```python
import torch

def _softmax(x, axis=-1):
    return torch.softmax(x, dim=axis)
def _gelu(x):
    return torch.nn.functional.gelu(x, approximate="tanh")
def _silu(x):
    return torch.nn.functional.silu(x)
def _sigmoid(x):
    return torch.sigmoid(x)
def _layernorm(x, axis=-1, eps=1e-5):
    m = x.mean(dim=axis, keepdim=True)
    v = x.var(dim=axis, keepdim=True, unbiased=False)
    return (x - m) / torch.sqrt(v + eps)
def _scatter_add(tgt, idx, src, axis=0):
    return tgt.clone().index_add_(axis, idx, src)
def _segment_sum(src, seg, n):
    out = torch.zeros((n,) + src.shape[1:], dtype=src.dtype)
    return out.index_add_(0, seg, src)
def _pad(x, pw):
    flat = tuple(v for pair in reversed(pw) for v in pair)
    return torch.nn.functional.pad(x, flat)

kernel_name = 'gated_mix__spectral_gfnet__glu_gated_reglu__prompt'

def setup_inputs():

    _w = (lambda a: (lambda t: t.to(torch.bfloat16) if t.is_floating_point() else t)(torch.as_tensor(a)))
    def _A_setup():
        B, S, D = 1, 2048, 512
        Df = D // 2 + 1
        return {
            "x": _w((lambda *s: torch.randn(*s, dtype=torch.bfloat16) * 0.05)(B, S, D)),
            "w_r": _w((lambda *s: torch.randn(*s, dtype=torch.bfloat16) * 0.05)(S, Df) * 0.02),
            "w_i": _w((lambda *s: torch.randn(*s, dtype=torch.bfloat16) * 0.05)(S, Df) * 0.02),
        }
    _A_in = _A_setup()

    def _B_setup():
        B, S, D, F = 1, 2048, 512, 1792
        return {
            "x": _w((lambda *s: torch.randn(*s, dtype=torch.bfloat16) * 0.05)(B, S, D)),
            "W_gate": _w((lambda *s: torch.randn(*s, dtype=torch.bfloat16) * 0.2)(D, F) * (2.0 / D) ** 0.5),
            "W_up": _w((lambda *s: torch.randn(*s, dtype=torch.bfloat16) * 0.2)(D, F) * (2.0 / D) ** 0.5),
            "W_down": _w((lambda *s: torch.randn(*s, dtype=torch.bfloat16) * 0.2)(F, D) * (1.0 / F) ** 0.5),
        }
    _B_in = _B_setup()

    return {
        "A_x": _A_in["x"],
        "A_w_r": _A_in["w_r"],
        "A_w_i": _A_in["w_i"],
        "B_x": _B_in["x"],
        "B_W_gate": _B_in["W_gate"],
        "B_W_up": _B_in["W_up"],
        "B_W_down": _B_in["W_down"],
        "gate_w": _w((lambda *s: torch.randn(*s, dtype=torch.bfloat16) * 0.05)(512) * 16.0),
    }

def reference(A_x, A_w_r, A_w_i, B_x, B_W_gate, B_W_up, B_W_down, gate_w):
    def _A_ref(x, w_r, w_i):
        B, S, D = x.shape
        X = (lambda x, axes=(-2,-1): torch.fft.rfft2(x.float(), dim=axes))(x, axes=(-2, -1))
        W = w_r + 1j * w_i
        X = X * W
        y = (lambda x, s, axes=(-2,-1): torch.fft.irfft2(x, s=s, dim=axes).to(torch.bfloat16))(X, (S, D), axes=(-2, -1))
        return y

    def _B_ref(x, W_gate, W_up, W_down):
        gate = torch.einsum("bsd,df->bsf", x, W_gate)
        up = torch.einsum("bsd,df->bsf", x, W_up)
        gate = gate * (lambda x, dt: x.to(dt))(gate > 0, gate.dtype)
        h = gate * up
        return torch.einsum("bsf,fd->bsd", h, W_down)

    x = A_x
    g = _sigmoid((x * gate_w).sum(-1, keepdims=True))
    a = _A_ref(x, A_w_r, A_w_i)
    b = _B_ref(x, B_W_gate, B_W_up, B_W_down)
    return g * a + (1 - g) * b
```

```cpp
#include <cuda_runtime.h>
#include <cuda_bf16.h>
#include <cuda_fp16.h>
#include <cuda.h>
#include <stdint.h>

namespace {

constexpr uint32_t OFF_X   = 0;
constexpr uint32_t OFF_R   = 131072;
constexpr uint32_t OFF_ST  = 196608;
constexpr uint32_t OFF_FF  = 212992;
constexpr uint32_t OFF_NST = OFF_R + 32768;
constexpr uint32_t OFF_TW2 = 229376;
constexpr uint32_t OFF_G   = 230400;
constexpr uint32_t OFF_ZERO = OFF_G - 512;
constexpr uint32_t OFF_BAR = 230912;
constexpr uint32_t SMEM_BYTES = 231424;

enum : uint32_t {
  B_XFULL = 0, B_RFULL = 8, B_REMPTY = 16, B_G2FULL = 20, B_G2EMPTY = 26, B_STFULL = 32, B_STEMPTY = 37,
  B_GFULL = 42, B_GDONE = 43, B_REDFULL = 44, B_PEER = 46, B_FFFREE = 47, B_WFULL = 48, B_TABFREE = 49, B_YRDY = 50, B_WRDY = 51, B_TROW = 52, B_COUNT = 53
};
constexpr uint32_t OFF_READY = OFF_BAR + 8 * B_COUNT;
constexpr uint32_t OFF_EXP = OFF_READY + 4;

__device__ __align__(1024) uint32_t g_Y[256 * 2048];
__device__ __align__(1024) uint8_t g_H[16 * 28 * 16384];
__device__ __align__(1024) uint16_t g_Z[512 * 2048];
__device__ __align__(1024) uint8_t g_T[8 * 4 * 8192];
__device__ __align__(128) float g_G[2048];
__device__ __align__(128) unsigned g_Sync[130 * 32];
__device__ __align__(128) unsigned g_Rdy[32 * 32];
__device__ __align__(128) unsigned g_Fin[16 * 32];
__device__ __align__(1024) uint4 g_W[129 * 128 * 8];

#define TS(i) do { } while (0)
#define TSP(i, pr) do { } while (0)
#define TS_END() do { } while (0)

__device__ __forceinline__ uint32_t smem_u32(const void* p) { return (uint32_t)__cvta_generic_to_shared(p); }
__device__ __forceinline__ void mbar_init(uint32_t bar, uint32_t cnt) {
  asm volatile("mbarrier.init.shared::cta.b64 [%0], %1;" ::"r"(bar), "r"(cnt) : "memory");
}
__device__ __forceinline__ void mbar_expect_tx(uint32_t bar, uint32_t bytes) {
  asm volatile("mbarrier.arrive.expect_tx.shared::cta.b64 _, [%0], %1;" ::"r"(bar), "r"(bytes) : "memory");
}
__device__ __forceinline__ void mbar_arrive(uint32_t bar) {
  asm volatile("mbarrier.arrive.shared::cta.b64 _, [%0];" ::"r"(bar) : "memory");
}
__device__ __forceinline__ void mbar_arrive_if(uint32_t bar, bool pred) {
  asm volatile("{\n.reg .pred p;\nsetp.ne.u32 p, %1, 0;\n@p mbarrier.arrive.shared::cta.b64 _, [%0];\n}" ::"r"(bar), "r"((uint32_t)pred) : "memory");
}
__device__ __forceinline__ void mbar_arrive_remote_if(uint32_t bar, bool pred) {
  asm volatile("{\n.reg .pred p;\nsetp.ne.u32 p, %1, 0;\n@p mbarrier.arrive.shared::cluster.b64 _, [%0];\n}" ::"r"(bar), "r"((uint32_t)pred) : "memory");
}
__device__ __forceinline__ uint32_t mapa(uint32_t addr, uint32_t cta) {
  uint32_t r;
  asm volatile("mapa.shared::cluster.u32 %0, %1, %2;" : "=r"(r) : "r"(addr), "r"(cta));
  return r;
}
__device__ __forceinline__ void mbar_arrive_remote(uint32_t remote_bar) {
  asm volatile("mbarrier.arrive.release.cluster.shared::cluster.b64 _, [%0];" ::"r"(remote_bar) : "memory");
}
__device__ __forceinline__ void mbar_arrive_remote_light(uint32_t remote_bar) {
  asm volatile("mbarrier.arrive.shared::cluster.b64 _, [%0];" ::"r"(remote_bar) : "memory");
}
__device__ __forceinline__ bool mbar_try(uint32_t bar, uint32_t parity) {
  uint32_t ok;
  asm volatile("{\n.reg .pred p;\nmbarrier.try_wait.parity.shared::cta.b64 p, [%1], %2;\nselp.u32 %0, 1, 0, p;\n}"
               : "=r"(ok) : "r"(bar), "r"(parity) : "memory");
  return ok != 0;
}
__device__ __forceinline__ bool mbar_test(uint32_t bar, uint32_t parity) {
  uint32_t ok;
  asm volatile("{\n.reg .pred p;\nmbarrier.test_wait.parity.shared::cta.b64 p, [%1], %2;\nselp.u32 %0, 1, 0, p;\n}"
               : "=r"(ok) : "r"(bar), "r"(parity) : "memory");
  return ok != 0;
}
__device__ __forceinline__ bool mbar_try_cluster(uint32_t bar, uint32_t parity) {
  uint32_t ok;
  asm volatile("{\n.reg .pred p;\nmbarrier.try_wait.parity.acquire.cluster.shared::cta.b64 p, [%1], %2;\nselp.u32 %0, 1, 0, p;\n}"
               : "=r"(ok) : "r"(bar), "r"(parity) : "memory");
  return ok != 0;
}
#define W_GATE 3
#define NPOLL 1
#define LATE_PIECE 4096
#define Z_PIECE 4096
#define Y_PACE 0
#define Y_DIRECT 1
#define Z_DIRECT 1
#define X_PREFETCH 1
#define ST_PIECE 4096
constexpr uint32_t SPIN_LIMIT = 1u << 24;
__device__ __forceinline__ void mbar_wait(uint32_t bar, uint32_t parity) {
  uint32_t n = 0;
  while (!mbar_try(bar, parity)) { if (++n > SPIN_LIMIT) __trap(); }
}
__device__ __forceinline__ void mbar_wait_u(uint32_t bar, uint32_t parity) {
  uint32_t n = 0;
  while (!__all_sync(0xffffffffu, mbar_try(bar, parity))) { if (++n > SPIN_LIMIT) __trap(); }
}
__device__ __forceinline__ void mbar_wait_cluster(uint32_t bar, uint32_t parity) {
  uint32_t n = 0;
  while (!mbar_try_cluster(bar, parity)) { if (++n > SPIN_LIMIT) __trap(); }
}
__device__ __forceinline__ void tma2d(uint32_t dst, const CUtensorMap* m, int c0, int c1, uint32_t bar) {
  asm volatile("cp.async.bulk.tensor.2d.shared::cluster.global.mbarrier::complete_tx::bytes [%0], [%1, {%3, %4}], [%2];"
               ::"r"(dst), "l"(m), "r"(bar), "r"(c0), "r"(c1) : "memory");
}
__device__ __forceinline__ void tma2d_mc(uint32_t dst, const CUtensorMap* m, int c0, int c1, uint32_t bar) {
  asm volatile("cp.async.bulk.tensor.2d.shared::cluster.global.mbarrier::complete_tx::bytes.multicast::cluster [%0], [%1, {%3, %4}], [%2], %5;"
               ::"r"(dst), "l"(m), "r"(bar), "r"(c0), "r"(c1), "h"((uint16_t)3) : "memory");
}
__device__ __forceinline__ void bulk_load(uint32_t dst, const void* src, uint32_t bytes, uint32_t bar) {
  asm volatile("cp.async.bulk.shared::cluster.global.mbarrier::complete_tx::bytes [%0], [%1], %2, [%3];"
               ::"r"(dst), "l"(src), "r"(bytes), "r"(bar) : "memory");
}
#define ELECT "{\n.reg .pred e;\nelect.sync _|e, 0xffffffff;\n@e "
__device__ __forceinline__ void mbar_expect_tx_e(uint32_t bar, uint32_t bytes) {
  asm volatile(ELECT "mbarrier.arrive.expect_tx.shared::cta.b64 _, [%0], %1;\n}" ::"r"(bar), "r"(bytes) : "memory");
}
__device__ __forceinline__ void tma2d_e(uint32_t dst, const CUtensorMap* m, int c0, int c1, uint32_t bar) {
  asm volatile(ELECT "cp.async.bulk.tensor.2d.shared::cluster.global.mbarrier::complete_tx::bytes [%0], [%1, {%3, %4}], [%2];\n}"
               ::"r"(dst), "l"(m), "r"(bar), "r"(c0), "r"(c1) : "memory");
}
__device__ __forceinline__ void tma2d_mc_e(uint32_t dst, const CUtensorMap* m, int c0, int c1, uint32_t bar) {
  asm volatile(ELECT "cp.async.bulk.tensor.2d.shared::cluster.global.mbarrier::complete_tx::bytes.multicast::cluster [%0], [%1, {%3, %4}], [%2], %5;\n}"
               ::"r"(dst), "l"(m), "r"(bar), "r"(c0), "r"(c1), "h"((uint16_t)3) : "memory");
}
__device__ __forceinline__ void bulk_load_e(uint32_t dst, const void* src, uint32_t bytes, uint32_t bar) {
  asm volatile(ELECT "cp.async.bulk.shared::cluster.global.mbarrier::complete_tx::bytes [%0], [%1], %2, [%3];\n}"
               ::"r"(dst), "l"(src), "r"(bytes), "r"(bar) : "memory");
}
__device__ __forceinline__ void bulk_store(void* dst, uint32_t src, uint32_t bytes) {
  asm volatile("cp.async.bulk.global.shared::cta.bulk_group [%0], [%1], %2;" ::"l"(dst), "r"(src), "r"(bytes) : "memory");
}
__device__ __forceinline__ void tma2d_store(const CUtensorMap* m, int c0, int c1, uint32_t src) {
  asm volatile("cp.async.bulk.tensor.2d.global.shared::cta.bulk_group [%0, {%1, %2}], [%3];"
               ::"l"(m), "r"(c0), "r"(c1), "r"(src) : "memory");
}
__device__ __forceinline__ void tma2d_prefetch(const CUtensorMap* m, int c0, int c1) {
  asm volatile("cp.async.bulk.prefetch.tensor.2d.L2.global [%0, {%1, %2}];" ::"l"(m), "r"(c0), "r"(c1) : "memory");
}
__device__ __forceinline__ void bulk_commit() { asm volatile("cp.async.bulk.commit_group;" ::: "memory"); }
__device__ __forceinline__ void bulk_wait_read() { asm volatile("cp.async.bulk.wait_group.read 0;" ::: "memory"); }
__device__ __forceinline__ void bulk_wait_all() { asm volatile("cp.async.bulk.wait_group 0;" ::: "memory"); }
__device__ __forceinline__ void cluster_arrive() { asm volatile("barrier.cluster.arrive.relaxed.aligned;" ::: "memory"); }
__device__ __forceinline__ void cluster_wait() { asm volatile("barrier.cluster.wait.acquire.aligned;" ::: "memory"); }
__device__ __forceinline__ uint32_t ld_volatile_shared(uint32_t addr) {
  uint32_t v;
  asm volatile("ld.volatile.shared.b32 %0, [%1];" : "=r"(v) : "r"(addr) : "memory");
  return v;
}
__device__ __forceinline__ unsigned ld_relaxed(const unsigned* p) {
  unsigned v;
  asm volatile("ld.relaxed.gpu.global.u32 %0, [%1];" : "=r"(v) : "l"(p) : "memory");
  return v;
}
__device__ __forceinline__ void bulk_prefetch(const void* src, uint32_t bytes) {
  asm volatile("cp.async.bulk.prefetch.L2.global [%0], %1;" ::"l"(src), "r"(bytes) : "memory");
}
__device__ __forceinline__ void fence_async_smem() { asm volatile("fence.proxy.async.shared::cta;" ::: "memory"); }
__device__ __forceinline__ void fence_async_all() { asm volatile("fence.proxy.async;" ::: "memory"); }
__device__ __forceinline__ unsigned ld_acquire(const unsigned* p) {
  unsigned v;
  asm volatile("ld.acquire.gpu.global.u32 %0, [%1];" : "=r"(v) : "l"(p) : "memory");
  return v;
}
__device__ __forceinline__ void red_release(unsigned* p) {
  asm volatile("red.release.gpu.global.add.u32 [%0], 1;" ::"l"(p) : "memory");
}
__device__ __forceinline__ void red_relaxed(unsigned* p) {
  asm volatile("red.relaxed.gpu.global.add.u32 [%0], 1;" ::"l"(p) : "memory");
}
__device__ __forceinline__ bool arrive_is_last(unsigned* p, unsigned target) {
  unsigned old;
  asm volatile("atom.relaxed.gpu.global.add.u32 %0, [%1], 1;" : "=r"(old) : "l"(p) : "memory");
  return old + 1 == target;
}
__device__ __forceinline__ void st_relaxed(unsigned* p, unsigned v) {
  asm volatile("st.relaxed.gpu.global.u32 [%0], %1;" ::"l"(p), "r"(v) : "memory");
}
__device__ __forceinline__ void poll_counter(const unsigned* p, unsigned target) {
  uint32_t n = 0;
  while ((int)(ld_relaxed(p) - target) < 0) { if (++n > SPIN_LIMIT) __trap(); }
}
__device__ __forceinline__ unsigned poll_tagged(const unsigned* p, unsigned e) {
  uint32_t n = 0;
  unsigned v;
  while (((v = ld_relaxed(p)) >> 16) != (e & 0xFFFFu)) { if (++n > SPIN_LIMIT) __trap(); }
  return v;
}
__device__ __forceinline__ void bar_sync(int id, int n) { asm volatile("bar.sync %0, %1;" ::"r"(id), "r"(n) : "memory"); }
__device__ __forceinline__ void bar_arrive(int id, int n) { asm volatile("bar.arrive %0, %1;" ::"r"(id), "r"(n) : "memory"); }
__device__ __forceinline__ void wgmma_fence() { asm volatile("wgmma.fence.sync.aligned;" ::: "memory"); }
__device__ __forceinline__ void wgmma_commit() { asm volatile("wgmma.commit_group.sync.aligned;" ::: "memory"); }
template <int N> __device__ __forceinline__ void wgmma_wait() { asm volatile("wgmma.wait_group.sync.aligned %0;" ::"n"(N) : "memory"); }
constexpr uint32_t HI128 = 0x40000040u, HI64 = 0x80000020u;
__device__ __forceinline__ uint32_t desc_k(uint32_t addr) { return ((addr & 0x3FFFF) >> 4) | (1u << 16); }
__device__ __forceinline__ uint32_t desc_mn(uint32_t addr) { return ((addr & 0x3FFFF) >> 4) | (512u << 16); }
template <int TA, int TB, int SA = 1>
__device__ __forceinline__ void wgmma_n128(float (&d)[64], uint32_t da, uint32_t db, int scale_d, uint32_t ahi = HI128) {
  asm volatile(
      "{\n.reg .pred p;\n.reg .b64 da, db;\nsetp.ne.b32 p, %66, 0;\n"
      "mov.b64 da, {%64, %70};\nmov.b64 db, {%65, 0x40000040};\n"
      "wgmma.mma_async.sync.aligned.m64n128k16.f32.bf16.bf16 "
      "{%0, %1, %2, %3, %4, %5, %6, %7, %8, %9, %10, %11, %12, %13, %14, %15, %16, %17, %18, %19, %20, %21, %22, %23, %24, %25, %26, %27, %28, %29, %30, %31, %32, %33, %34, %35, %36, %37, %38, %39, %40, %41, %42, %43, %44, %45, %46, %47, %48, %49, %50, %51, %52, %53, %54, %55, %56, %57, %58, %59, %60, %61, %62, %63}, "
      "da, db, p, %69, 1, %67, %68;\n}\n"
      :
      "+f"(d[0]), "+f"(d[1]), "+f"(d[2]), "+f"(d[3]), "+f"(d[4]), "+f"(d[5]), "+f"(d[6]), "+f"(d[7]),
      "+f"(d[8]), "+f"(d[9]), "+f"(d[10]), "+f"(d[11]), "+f"(d[12]), "+f"(d[13]), "+f"(d[14]), "+f"(d[15]),
      "+f"(d[16]), "+f"(d[17]), "+f"(d[18]), "+f"(d[19]), "+f"(d[20]), "+f"(d[21]), "+f"(d[22]), "+f"(d[23]),
      "+f"(d[24]), "+f"(d[25]), "+f"(d[26]), "+f"(d[27]), "+f"(d[28]), "+f"(d[29]), "+f"(d[30]), "+f"(d[31]),
      "+f"(d[32]), "+f"(d[33]), "+f"(d[34]), "+f"(d[35]), "+f"(d[36]), "+f"(d[37]), "+f"(d[38]), "+f"(d[39]),
      "+f"(d[40]), "+f"(d[41]), "+f"(d[42]), "+f"(d[43]), "+f"(d[44]), "+f"(d[45]), "+f"(d[46]), "+f"(d[47]),
      "+f"(d[48]), "+f"(d[49]), "+f"(d[50]), "+f"(d[51]), "+f"(d[52]), "+f"(d[53]), "+f"(d[54]), "+f"(d[55]),
      "+f"(d[56]), "+f"(d[57]), "+f"(d[58]), "+f"(d[59]), "+f"(d[60]), "+f"(d[61]), "+f"(d[62]), "+f"(d[63])
      : "r"(da), "r"(db), "r"(scale_d), "n"(TA), "n"(TB), "n"(SA), "r"(ahi));
}
__device__ __forceinline__ void wgmma_n64_bf(float (&d)[32], uint32_t da, uint32_t db, int scale_d) {
  asm volatile(
      "{\n.reg .pred p;\n.reg .b64 da, db;\nsetp.ne.b32 p, %34, 0;\n"
      "mov.b64 da, {%32, 0x40000040};\nmov.b64 db, {%33, 0x40000040};\n"
      "wgmma.mma_async.sync.aligned.m64n64k16.f32.bf16.bf16 "
      "{%0, %1, %2, %3, %4, %5, %6, %7, %8, %9, %10, %11, %12, %13, %14, %15, %16, %17, %18, %19, %20, %21, %22, %23, %24, %25, %26, %27, %28, %29, %30, %31}, "
      "da, db, p, 1, 1, 0, 1;\n}\n"
      :
      "+f"(d[0]), "+f"(d[1]), "+f"(d[2]), "+f"(d[3]), "+f"(d[4]), "+f"(d[5]), "+f"(d[6]), "+f"(d[7]),
      "+f"(d[8]), "+f"(d[9]), "+f"(d[10]), "+f"(d[11]), "+f"(d[12]), "+f"(d[13]), "+f"(d[14]), "+f"(d[15]),
      "+f"(d[16]), "+f"(d[17]), "+f"(d[18]), "+f"(d[19]), "+f"(d[20]), "+f"(d[21]), "+f"(d[22]), "+f"(d[23]),
      "+f"(d[24]), "+f"(d[25]), "+f"(d[26]), "+f"(d[27]), "+f"(d[28]), "+f"(d[29]), "+f"(d[30]), "+f"(d[31])
      : "r"(da), "r"(db), "r"(scale_d));
}
__device__ __forceinline__ void wgmma_n64_f16t(float (&d)[32], uint32_t da, uint32_t db, int scale_d) {
  asm volatile(
      "{\n.reg .pred p;\n.reg .b64 da, db;\nsetp.ne.b32 p, %34, 0;\n"
      "mov.b64 da, {%32, 0x40000040};\nmov.b64 db, {%33, 0x40000040};\n"
      "wgmma.mma_async.sync.aligned.m64n64k16.f32.f16.f16 "
      "{%0, %1, %2, %3, %4, %5, %6, %7, %8, %9, %10, %11, %12, %13, %14, %15, %16, %17, %18, %19, %20, %21, %22, %23, %24, %25, %26, %27, %28, %29, %30, %31}, "
      "da, db, p, 1, 1, 1, 1;\n}\n"
      :
      "+f"(d[0]), "+f"(d[1]), "+f"(d[2]), "+f"(d[3]), "+f"(d[4]), "+f"(d[5]), "+f"(d[6]), "+f"(d[7]),
      "+f"(d[8]), "+f"(d[9]), "+f"(d[10]), "+f"(d[11]), "+f"(d[12]), "+f"(d[13]), "+f"(d[14]), "+f"(d[15]),
      "+f"(d[16]), "+f"(d[17]), "+f"(d[18]), "+f"(d[19]), "+f"(d[20]), "+f"(d[21]), "+f"(d[22]), "+f"(d[23]),
      "+f"(d[24]), "+f"(d[25]), "+f"(d[26]), "+f"(d[27]), "+f"(d[28]), "+f"(d[29]), "+f"(d[30]), "+f"(d[31])
      : "r"(da), "r"(db), "r"(scale_d));
}
__device__ __forceinline__ uint32_t pack_bf16(float lo, float hi) {
  uint32_t r;
  asm("cvt.rn.bf16x2.f32 %0, %1, %2;" : "=r"(r) : "f"(hi), "f"(lo));
  return r;
}
__device__ __forceinline__ uint32_t pack_bf16_relu(float lo, float hi) {
  uint32_t r;
  asm("cvt.rn.relu.bf16x2.f32 %0, %1, %2;" : "=r"(r) : "f"(hi), "f"(lo));
  return r;
}
__device__ __forceinline__ uint32_t mul_bf16x2(uint32_t a, uint32_t b) {
  uint32_t r;
  asm("mul.rn.bf16x2 %0, %1, %2;" : "=r"(r) : "r"(a), "r"(b));
  return r;
}
__device__ __forceinline__ void stmatrix_x4(uint32_t addr, uint32_t r0, uint32_t r1, uint32_t r2, uint32_t r3) {
  asm volatile("stmatrix.sync.aligned.m8n8.x4.shared.b16 [%0], {%1, %2, %3, %4};"
               ::"r"(addr), "r"(r0), "r"(r1), "r"(r2), "r"(r3) : "memory");
}
__device__ __forceinline__ void sts128(uint32_t addr, uint32_t a, uint32_t b, uint32_t c, uint32_t d) {
  asm volatile("st.shared.v4.b32 [%0], {%1, %2, %3, %4};" ::"r"(addr), "r"(a), "r"(b), "r"(c), "r"(d) : "memory");
}
__device__ __forceinline__ uint4 lds128(uint32_t addr) {
  uint4 v;
  asm volatile("ld.shared.v4.b32 {%0, %1, %2, %3}, [%4];" : "=r"(v.x), "=r"(v.y), "=r"(v.z), "=r"(v.w) : "r"(addr) : "memory");
  return v;
}
__device__ __forceinline__ float bf_lo(uint32_t v) { return __uint_as_float(v << 16); }
__device__ __forceinline__ float bf_hi(uint32_t v) { return __uint_as_float(v & 0xFFFF0000u); }

struct C2 { __half2 x, y; };
__device__ __forceinline__ C2 cadd(C2 a, C2 b) { return {__hadd2(a.x, b.x), __hadd2(a.y, b.y)}; }
__device__ __forceinline__ C2 csub(C2 a, C2 b) { return {__hsub2(a.x, b.x), __hsub2(a.y, b.y)}; }
template <int SG> __device__ __forceinline__ C2 cmul(C2 a, __half2 c, __half2 s) {
  return SG > 0 ? C2{__hfma2(a.x, c, __hneg2(__hmul2(a.y, s))), __hfma2(a.x, s, __hmul2(a.y, c))}
                : C2{__hfma2(a.x, c, __hmul2(a.y, s)), __hfma2(a.y, c, __hneg2(__hmul2(a.x, s)))};
}
template <int SG> __device__ __forceinline__ C2 ctw(C2 a, __half2 w) { return cmul<SG>(a, __low2half2(w), __high2half2(w)); }
template <int SG> __device__ __forceinline__ C2 mul_i(C2 a) {
  return SG > 0 ? C2{__hneg2(a.y), a.x} : C2{a.y, __hneg2(a.x)};
}
template <int SG> __device__ __forceinline__ void fft4(C2& a0, C2& a1, C2& a2, C2& a3) {
  C2 t0 = cadd(a0, a2), t1 = csub(a0, a2), t2 = cadd(a1, a3), d = csub(a1, a3);
  a0 = cadd(t0, t2); a2 = csub(t0, t2);
  if (SG > 0) { a1 = {__hsub2(t1.x, d.y), __hadd2(t1.y, d.x)}; a3 = {__hadd2(t1.x, d.y), __hsub2(t1.y, d.x)}; }
  else        { a1 = {__hadd2(t1.x, d.y), __hsub2(t1.y, d.x)}; a3 = {__hsub2(t1.x, d.y), __hadd2(t1.y, d.x)}; }
}
template <int SG> __device__ __forceinline__ void fft16(C2 (&v)[16]) {
  const __half2 C1 = __float2half2_rn(0.92387953251128674f), S1 = __float2half2_rn(0.38268343236508977f);
  const __half2 R = __float2half2_rn(0.70710678118654752f), NR = __float2half2_rn(-0.70710678118654752f);
  const __half2 NC1 = __float2half2_rn(-0.92387953251128674f), NS1 = __float2half2_rn(-0.38268343236508977f);
#pragma unroll
  for (int b = 0; b < 4; b++) fft4<SG>(v[b], v[4 + b], v[8 + b], v[12 + b]);
  v[5]  = cmul<SG>(v[5], C1, S1);
  v[6]  = cmul<SG>(v[6], R, R);
  v[7]  = cmul<SG>(v[7], S1, C1);
  v[9]  = cmul<SG>(v[9], R, R);
  v[10] = mul_i<SG>(v[10]);
  v[11] = cmul<SG>(v[11], NR, R);
  v[13] = cmul<SG>(v[13], S1, C1);
  v[14] = cmul<SG>(v[14], NR, R);
  v[15] = cmul<SG>(v[15], NC1, NS1);
#pragma unroll
  for (int c = 0; c < 4; c++) fft4<SG>(v[4 * c], v[4 * c + 1], v[4 * c + 2], v[4 * c + 3]);
  C2 t;
  t = v[1]; v[1] = v[4]; v[4] = t;   t = v[2]; v[2] = v[8]; v[8] = t;   t = v[3]; v[3] = v[12]; v[12] = t;
  t = v[6]; v[6] = v[9]; v[9] = t;   t = v[7]; v[7] = v[13]; v[13] = t; t = v[11]; v[11] = v[14]; v[14] = t;
}
template <int SG> __device__ __forceinline__ void fft8(C2* v) {
  const __half2 R = __float2half2_rn(0.70710678118654752f), NR = __float2half2_rn(-0.70710678118654752f);
  C2 e[4], o[4];
#pragma unroll
  for (int b = 0; b < 4; b++) { e[b] = cadd(v[b], v[4 + b]); o[b] = csub(v[b], v[4 + b]); }
  o[1] = cmul<SG>(o[1], R, R);
  o[2] = mul_i<SG>(o[2]);
  o[3] = cmul<SG>(o[3], NR, R);
  fft4<SG>(e[0], e[1], e[2], e[3]);
  fft4<SG>(o[0], o[1], o[2], o[3]);
#pragma unroll
  for (int d = 0; d < 4; d++) { v[2 * d] = e[d]; v[2 * d + 1] = o[d]; }
}
__device__ __forceinline__ uint32_t h2u(__half2 h) { return *reinterpret_cast<uint32_t*>(&h); }
__device__ __forceinline__ __half2 u2h(uint32_t u) { return *reinterpret_cast<__half2*>(&u); }
__device__ __forceinline__ void sts_c2(uint32_t addr, C2 v) {
  asm volatile("st.shared.v2.b32 [%0], {%1, %2};" ::"r"(addr), "r"(h2u(v.x)), "r"(h2u(v.y)) : "memory");
}
__device__ __forceinline__ C2 lds_c2(uint32_t addr) {
  uint32_t a, b;
  asm volatile("ld.shared.v2.b32 {%0, %1}, [%2];" : "=r"(a), "=r"(b) : "r"(addr) : "memory");
  return C2{u2h(a), u2h(b)};
}
__device__ __forceinline__ uint32_t bf2_to_h2(uint32_t w, uint32_t nbias) {
  return (__viaddmax_s16x2(w & 0x7FFF7FFFu, nbias, 0u) << 3) | (w & 0x80008000u);
}
template <int N> __device__ __forceinline__ uint32_t acc_max_exp(uint32_t m, const uint32_t (&w)[N]) {
#pragma unroll
  for (int i = 0; i < N; i += 2) m = __vimax3_s16x2(m, w[i] & 0x7F807F80u, w[i + 1] & 0x7F807F80u);
  return m;
}
__device__ __forceinline__ uint32_t warp_max_exp(uint32_t m) { return __reduce_max_sync(0xffffffffu, max(m >> 23, (m & 0xFFFFu) >> 7)); }

__device__ __forceinline__ uint32_t g2_buf(int b) {
  return ((0x532410u >> (4 * b)) & 7u) * 32768u;
}

__device__ __forceinline__ uint32_t g2_seq(int i) { return (uint32_t)(0x210cb5a9843210ull >> (4 * i)) & 15u; }
__device__ __forceinline__ int g1_chunk(int j, int tile) { return 7 * (j >> 1) + (tile == 3 ? 6 : 3 * (j & 1) + tile); }
__device__ __forceinline__ int g2_chunk(int kh, int i) {
  return i < 10 ? 7 * (i & 3) + 3 * kh + (i >> 2) : i < 12 ? 7 * (2 * kh + i - 10) + 6 : i < 14 ? 7 * (i - 10) + 3 * kh + 2 : 2 * (i - 14) + kh;
}

__device__ __forceinline__ void epi_h(const float (&a)[64], uint32_t st_addr, int lane) {
#pragma unroll
  for (int jb = 0; jb < 8; jb += 2) {
    uint32_t r[4];
#pragma unroll
    for (int q = 0; q < 4; q++) {
      int i = 4 * jb + 2 * q;
      r[q] = mul_bf16x2(pack_bf16_relu(a[i], a[i + 1]), pack_bf16(a[32 + i], a[32 + i + 1]));
    }
    uint32_t grp = jb + (lane >> 4);
    stmatrix_x4(st_addr + ((grp ^ (lane & 7)) << 4), r[0], r[1], r[2], r[3]);
  }
}

__global__ void __cluster_dims__(2, 1, 1) __launch_bounds__(512, 1)
fused_kernel(const __grid_constant__ CUtensorMap map_x, const __grid_constant__ CUtensorMap map_wg,
             const __grid_constant__ CUtensorMap map_wu, const __grid_constant__ CUtensorMap map_wd,
             const __grid_constant__ CUtensorMap map_y, const __grid_constant__ CUtensorMap map_z,
             const __grid_constant__ CUtensorMap map_w, const __grid_constant__ CUtensorMap map_gn,
             const __grid_constant__ CUtensorMap map_un, const __grid_constant__ CUtensorMap map_o,
             const __nv_bfloat16* __restrict__ x_ptr, const __nv_bfloat16* __restrict__ w_r, const __nv_bfloat16* __restrict__ w_i,
             const __nv_bfloat16* __restrict__ wd_ptr, const __nv_bfloat16* __restrict__ gate_w,
             __nv_bfloat16* __restrict__ out) {
  extern __shared__ __align__(1024) uint8_t smem[];
  const uint32_t sb = smem_u32(smem);
  const uint32_t bar0 = sb + OFF_BAR;
  const int tid = threadIdx.x, lane = tid & 31;
  const int warp = __shfl_sync(0xffffffffu, tid >> 5, 0);
  const int cl = blockIdx.x >> 1, kh = blockIdx.x & 1;
  int grp, p;
  if (cl < 4) { grp = 15; p = cl; }
  else if (cl < 36) { grp = (cl - 4) & 7; p = (cl - 4) >> 3; }
  else { grp = 8 + (cl - 36) % 7; p = (cl - 36) / 7; }
  const int kq = grp & 1, r = (grp & 14) + kh, j = 4 * kq + p;
  const bool extra = blockIdx.x >= 128;
#define BAR(i) (bar0 + 8u * (i))

  if (!extra) {
    if (warp == 15 && lane == 0) bulk_prefetch(x_ptr + (size_t)(r * 128 + 16 * j) * 512, 16384);
    if (warp == 12 && lane == 0) {
#pragma unroll
      for (int kk = 0; kk < 8; kk++) mbar_init(BAR(B_XFULL + kk), 1);
#pragma unroll 1
      for (int kk = 0; kk < 8; kk++) {
        mbar_expect_tx(BAR(B_XFULL + kk), 16384);
        tma2d(sb + OFF_X + kk * 16384, &map_x, kk * 64, r * 128, BAR(B_XFULL + kk));
      }
      asm volatile("fence.mbarrier_init.release.cluster;" ::: "memory");
      TS(55);
    }
    if (warp == 13 && lane == 0) {
#pragma unroll
      for (int i = B_RFULL; i < (int)B_COUNT; i++) {
        uint32_t cnt = 1;
        if (i >= (int)B_REMPTY && i < (int)B_G2FULL) cnt = 2;
        if (i >= (int)B_G2EMPTY && i < (int)B_STFULL) cnt = 4;
        if (i >= (int)B_STFULL && i < (int)B_STEMPTY) cnt = 128;
        if (i == (int)B_GFULL) cnt = 32;
        if (i == (int)B_WFULL || i == (int)B_TROW) cnt = 128;
        if (i == (int)B_GDONE) cnt = 4;
        mbar_init(BAR(i), cnt);
      }
      asm volatile("st.shared.b32 [%0], %1;" ::"r"(sb + OFF_READY), "r"(0) : "memory");
      asm volatile("fence.mbarrier_init.release.cluster;" ::: "memory");
      TS(54);
    }
    if (warp == 14 && lane == 0) {
      tma2d_prefetch(kh ? &map_wu : &map_wg, g1_chunk(j, 0) * 64, (r >> 1) * 64);
    }
    __syncwarp();
    cluster_arrive();
    if (warp < 8) {
      const int cc = 64 * (j >> 1) + 2 * lane + (j & 1), d0 = warp * 32;
      const float c2 = 2.0f * __cosf((float)cc * (3.14159265358979f / 256.0f));
      const uint32_t r7 = lane & 6;
      const uint32_t rowaddr = sb + OFF_ST + (warp >> 1) * 8192 + (uint32_t)(16 * (lane >> 3) + 8 * (lane & 1) + r7) * 128u;
#pragma unroll 1
      for (int u = 0; u < 4; u++) {
        uint32_t pc[4], ps[4];
        const int ph = cc * (d0 + 8 * u);
        const float an0 = (float)(ph & 511) * (-3.14159265358979f / 256.0f), an1 = (float)((ph + cc) & 511) * (-3.14159265358979f / 256.0f);
        float ca = __cosf(an0), cb = __cosf(an1), sa = __sinf(an0), sc = __sinf(an1);
#pragma unroll
        for (int e = 0; e < 4; e++) {
          pc[e] = pack_bf16(ca, cb);
          ps[e] = (cc == 0) ? 0xBF803F80u : pack_bf16(sa, sc);
          if (e < 3) {
            ca = c2 * cb - ca; cb = c2 * ca - cb;
            sa = c2 * sc - sa; sc = c2 * sa - sc;
          }
        }
        const uint32_t ch = (uint32_t)((warp & 1) * 4 + u) ^ r7;
        sts128(rowaddr + (ch << 4), pc[0], pc[1], pc[2], pc[3]);
        sts128(rowaddr + 128 + ((ch ^ 1) << 4), ps[0], ps[1], ps[2], ps[3]);
      }
      if (tid == 0) TS(14);
      fence_async_smem();
    }
  }

  if (warp < 8) {
    asm volatile("setmaxnreg.inc.sync.aligned.u32 168;");
    if (extra) return;
    const int wg = warp >> 2, w4 = warp & 3, t128 = tid & 127;
    bar_sync(4, 256);
    cluster_wait();
    if (tid == 0) TS(1);
    const uint32_t rempty_peer = mapa(BAR(B_REMPTY), kh ^ 1);
    const bool lead = t128 == 0;
#define RELEASE_SLOT(sl, pr) do { mbar_arrive_if(BAR(B_REMPTY + (sl)), pr); mbar_arrive_remote_if(rempty_peer + 8u * (sl), pr); } while (0)
#define RELEASE_BUF(b, pr) RELEASE_SLOT(B_G2EMPTY - B_REMPTY + (b), pr)
    float acc0[64], acc1[64];
    const uint32_t st_lane = sb + OFF_ST + (uint32_t)(16 * w4 + (lane & 7) + ((lane >> 3) & 1) * 8) * 128u;
    if (wg == 0) {
#pragma unroll 1
      for (int kk = 0; kk < 4; kk++) {
        mbar_wait_u(BAR(B_XFULL + kk), 0);
        TSP(2, lead && kk == 0);
        const uint32_t da = desc_k(sb + OFF_ST + kk * 8192), db = desc_k(sb + OFF_X + kk * 16384);
        wgmma_fence();
#pragma unroll
        for (int k = 0; k < 4; k++) wgmma_n128<0, 0>(acc0, da + 2 * k, db + 2 * k, (kk | k) != 0);
        wgmma_commit();
      }
      if (j & 1) {
#pragma unroll 1
        for (int kk = 0; kk < 4; kk++) {
          mbar_wait_u(BAR(B_XFULL + 4 + kk), 0);
          const uint32_t da = desc_k(sb + OFF_ST + kk * 8192), db = desc_k(sb + OFF_X + 65536 + kk * 16384);
          wgmma_fence();
#pragma unroll
          for (int k = 0; k < 4; k++) wgmma_n128<0, 0, -1>(acc0, da + 2 * k, db + 2 * k, 1);
          wgmma_commit();
        }
      } else {
#pragma unroll 1
        for (int kk = 0; kk < 4; kk++) {
          mbar_wait_u(BAR(B_XFULL + 4 + kk), 0);
          const uint32_t da = desc_k(sb + OFF_ST + kk * 8192), db = desc_k(sb + OFF_X + 65536 + kk * 16384);
          wgmma_fence();
#pragma unroll
          for (int k = 0; k < 4; k++) wgmma_n128<0, 0, 1>(acc0, da + 2 * k, db + 2 * k, 1);
          wgmma_commit();
        }
      }
      if (t128 == 0) TS(53);
      wgmma_wait<0>();
      if (t128 == 0) TS(3);
      bar_sync(5, 128);
      mbar_arrive_if(BAR(B_TABFREE), lead);
      const uint32_t yrow = sb + OFF_FF + (uint32_t)(8 * w4 + (lane >> 2)) * 128u;
#pragma unroll
      for (int g = 0; g < 4; g++) {
#pragma unroll
        for (int e = 0; e < 2; e++) {
          const uint32_t ch = (uint32_t)(2 * (lane & 3) + e) ^ (uint32_t)(lane >> 2);
          const int i0 = 16 * g + e;
          sts128(yrow + g * 4096 + (ch << 4), pack_bf16(acc0[i0], acc0[i0 + 2]), pack_bf16(acc0[i0 + 4], acc0[i0 + 6]),
                 pack_bf16(acc0[i0 + 8], acc0[i0 + 10]), pack_bf16(acc0[i0 + 12], acc0[i0 + 14]));
        }
      }
      fence_async_smem();
      mbar_arrive(BAR(B_STFULL + 0));
    }
#pragma unroll 1
    for (int t = wg ^ 1; t < 3; t += 2) {
#pragma unroll 1
      for (int kk = 0; kk < 8; kk++) {
        const uint32_t slot = kk & 3, par = (uint32_t)(kk >> 2);
        bool pend = kk > 0;
        if (!__all_sync(0xffffffffu, mbar_test(BAR(B_RFULL + wg * 4 + slot), par))) {
          wgmma_wait<0>();
          RELEASE_SLOT((kk - 1) & 3, lead && pend);
          pend = false;
          mbar_wait_u(BAR(B_RFULL + wg * 4 + slot), par);
        }
        if (t == 0) mbar_wait_u(BAR(B_XFULL + kk), 0);
        TSP(96 + t * 8 + kk, lead);
        const uint32_t da = desc_k(sb + OFF_X + kk * 16384), db = desc_mn(sb + OFF_R + slot * 16384);
        wgmma_fence();
#pragma unroll
        for (int k = 0; k < 4; k++) {
          wgmma_n128<0, 1>(acc0, da + 2 * k, db + 128 * k, (kk | k) != 0);
          wgmma_n128<0, 1>(acc1, da + 512 + 2 * k, db + 128 * k, (kk | k) != 0);
        }
        wgmma_commit();
        wgmma_wait<1>();
        RELEASE_SLOT((kk - 1) & 3, lead && pend);
        RELEASE_BUF((kk >> 1) - 1, lead && t == 2 && kk >= 2 && !(kk & 1));
        RELEASE_BUF(3, lead && t == 2 && kk == 6);
      }
      wgmma_wait<0>();
      RELEASE_SLOT(3, lead);
      RELEASE_BUF(4, lead && t == 2);
      RELEASE_BUF(5, lead && t == 2);
      TSP(4 + t, lead);
      mbar_wait_u(BAR(B_STEMPTY + 1 + t), 0);
      epi_h(acc0, st_lane, lane);
      epi_h(acc1, st_lane + 8192, lane);
      fence_async_smem();
      mbar_arrive(BAR(B_STFULL + 1 + t));
    }
    if (wg == 0) {
      mbar_wait_u(BAR(B_GDONE), 0);
#define N_RELEASE(st, pr) do { RELEASE_BUF((st) + ((st) >= 2), pr); RELEASE_BUF(2, (pr) && (st) == 1); } while (0)
#pragma unroll 1
      for (int st = 0; st < 4; st++) {
        bool pend = st > 0;
        if (!__all_sync(0xffffffffu, mbar_test(BAR(B_RFULL + st), 0))) {
          wgmma_wait<0>();
          N_RELEASE(st - 1, lead && pend);
          pend = false;
          mbar_wait_u(BAR(B_RFULL + st), 0);
        }
        TSP(120 + st, lead);
        const uint32_t da = desc_mn(sb + OFF_R + st * 16384), db = desc_k(sb + OFF_X + st * 32768);
        wgmma_fence();
#pragma unroll
        for (int k = 0; k < 8; k++) wgmma_n128<1, 0>(acc1, da + 64 * k, db + (k >> 2) * 1024 + 2 * (k & 3), (st | k) != 0, HI64);
        wgmma_commit();
        wgmma_wait<1>();
        N_RELEASE(st - 1, lead && pend);
      }
      wgmma_wait<0>();
      RELEASE_BUF(4, lead);
      TSP(7, lead);
      uint32_t keep[16];
      const uint32_t xs = sb + OFF_NST + 8192 + lane * 16;
      if (w4 < 2) {
#pragma unroll
        for (int i = 0; i < 4; i++)
          sts128(xs + w4 * 2048 + i * 512, pack_bf16_relu(acc1[32 + 8 * i], acc1[33 + 8 * i]), pack_bf16_relu(acc1[34 + 8 * i], acc1[35 + 8 * i]),
                 pack_bf16_relu(acc1[36 + 8 * i], acc1[37 + 8 * i]), pack_bf16_relu(acc1[38 + 8 * i], acc1[39 + 8 * i]));
#pragma unroll
        for (int i = 0; i < 16; i++) keep[i] = pack_bf16_relu(acc1[2 * i], acc1[2 * i + 1]);
      } else {
#pragma unroll
        for (int i = 0; i < 4; i++)
          sts128(xs + w4 * 2048 + i * 512, pack_bf16(acc1[8 * i], acc1[1 + 8 * i]), pack_bf16(acc1[2 + 8 * i], acc1[3 + 8 * i]),
                 pack_bf16(acc1[4 + 8 * i], acc1[5 + 8 * i]), pack_bf16(acc1[6 + 8 * i], acc1[7 + 8 * i]));
#pragma unroll
        for (int i = 0; i < 16; i++) keep[i] = pack_bf16(acc1[32 + 2 * i], acc1[33 + 2 * i]);
      }
      bar_sync(7, 128);
      const uint32_t hl = sb + OFF_NST + (uint32_t)(64 * (w4 >> 1) + 8 * (lane >> 4) + (lane & 7)) * 64u
                        + (((uint32_t)(2 * (w4 & 1) + ((lane >> 3) & 1)) ^ (uint32_t)((lane >> 1) & 3)) << 4);
#pragma unroll
      for (int i = 0; i < 4; i++) {
        const uint4 o = lds128(xs + (w4 ^ 2) * 2048 + i * 512);
        asm volatile("stmatrix.sync.aligned.m8n8.x4.trans.shared.b16 [%0], {%1, %2, %3, %4};"
                     ::"r"(hl + i * 1024), "r"(mul_bf16x2(keep[4 * i], o.x)), "r"(mul_bf16x2(keep[4 * i + 1], o.y)),
                       "r"(mul_bf16x2(keep[4 * i + 2], o.z)), "r"(mul_bf16x2(keep[4 * i + 3], o.w)) : "memory");
      }
      bar_arrive(1, 256);
      fence_async_smem();
      mbar_arrive(BAR(B_STFULL + 4));
    } else {
      bar_sync(1, 256);
    }
    TSP(8 + wg, lead);
    {
      uint32_t prev = 1;
#pragma unroll 1
      for (int i = 0; i < 12; i++) {
        const uint32_t bp = g2_seq(i), b = bp & 7u;
        mbar_wait_u(BAR(B_G2FULL + b), bp >> 3);
        const uint32_t buf = sb + g2_buf(b);
        const bool nar = i >= 10;
        const uint32_t da = desc_k(buf + wg * (nar ? 4096 : 8192)), db = desc_mn(buf + 16384);
        const uint32_t ahi = nar ? HI64 : HI128, mid = nar ? 512u : 4u;
        wgmma_fence();
#pragma unroll
        for (int k = 0; k < 4; k++) wgmma_n128<0, 1>(acc0, da + 2 * (k & 1) + (k >> 1) * mid, db + 128 * k, (i | k) != 0, ahi);
        wgmma_commit();
        wgmma_wait<1>();
        RELEASE_BUF(prev, lead && i != 0);
        prev = b;
      }
    }
    {
      float az[32], cs[32], ck[32];
#define HALF_STAGE(acc, i, boff, first) do {                                                                   \
        const uint32_t da = desc_k(sb + g2_buf(i) + wg * 8192), db = desc_mn(sb + g2_buf(i) + (boff));         \
        _Pragma("unroll") for (int k = 0; k < 4; k++) wgmma_n64_bf(acc, da + 2 * k, db + 128 * k, !(first) || k != 0); \
      } while (0)
#define Z_STAGE(i, first) do {                                                                                 \
        mbar_wait_u(BAR(B_G2FULL + (i)), (i) == 0 || (i) == 5);                                                \
        const uint32_t da = desc_mn(sb + g2_buf(i) + wg * 8192), db = desc_mn(sb + g2_buf(i) + 16384);         \
        wgmma_fence();                                                                                         \
        _Pragma("unroll") for (int k = 0; k < 4; k++) wgmma_n64_f16t(az, da + 128 * k, db + 128 * k, !(first) || k != 0); \
      } while (0)
      mbar_wait_u(BAR(B_G2FULL + 1), 0);
      wgmma_fence();
      HALF_STAGE(cs, 1, 24576, true);
      wgmma_commit();
      wgmma_wait<1>();
      RELEASE_BUF(0, lead);
      mbar_wait_u(BAR(B_G2FULL + 2), 0);
      wgmma_fence();
      HALF_STAGE(cs, 2, 24576, false);
      wgmma_commit();
      mbar_wait_u(BAR(B_GFULL), 0);
      const float* gs = reinterpret_cast<const float*>(smem + OFF_G);
      float g0 = gs[64 * wg + 16 * w4 + (lane >> 2)], g1 = gs[64 * wg + 16 * w4 + (lane >> 2) + 8];
      const float gb0 = 1.0f - g0, gb1 = 1.0f - g1;
      {
        const uint32_t ex = ld_volatile_shared(sb + OFF_EXP);
        const int ew = max((int)(ex & 0xFFu) - 14, 0), eref = max((int)((ex >> 8) & 0xFFu) - 2, 0);
        const float s1 = __uint_as_float((uint32_t)(ew + 6) << 23), s2 = __uint_as_float((uint32_t)min(eref + 5, 254) << 23);
        g0 = g0 * s1 * s2; g1 = g1 * s1 * s2;
      }
      const float gu0 = kq ? -g0 : g0, gu1 = kq ? -g1 : g1;
      const uint32_t stg = sb + g2_buf(5) + wg * 8192 + w4 * 2048;
      const uint32_t srow = stg + (uint32_t)(lane & 15) * 128u;
      const int orow = r * 128 + 64 * wg + 16 * w4;
      Z_STAGE(5, true);
      wgmma_commit();
      wgmma_wait<1>();
#pragma unroll
      for (int i = 0; i < 32; i++) acc0[32 + i] = ((i & 2) ? gb1 : gb0) * (acc0[32 + i] + cs[i]);
      Z_STAGE(3, false);
      Z_STAGE(4, false);
      Z_STAGE(0, false);
      wgmma_commit();
      HALF_STAGE(ck, 1, 16384, true);
      wgmma_commit();
      wgmma_wait<1>();
      if (t128 == 0) TS(10 + wg);
#pragma unroll
      for (int jb = 0; jb < 8; jb += 2) {
        uint32_t pk[4];
#pragma unroll
        for (int c = 0; c < 4; c++) {
          const int x = 4 * jb + 2 * c;
          const float g = (c & 1) ? gu1 : gu0;
          pk[c] = pack_bf16(g * az[x] + acc0[32 + x], g * az[x + 1] + acc0[33 + x]);
        }
        stmatrix_x4(srow + (((jb + (lane >> 4)) ^ (lane & 7)) << 4), pk[0], pk[1], pk[2], pk[3]);
      }
      wgmma_fence();
      HALF_STAGE(ck, 2, 16384, false);
      wgmma_commit();
      fence_async_smem();
      __syncwarp();
      asm volatile(ELECT "cp.reduce.async.bulk.tensor.2d.global.shared::cta.add.bulk_group [%0, {%1, %2}], [%3];\n}"
                   ::"l"(&map_o), "r"(p * 64 + 256), "r"(orow), "r"(stg) : "memory");
      if (t128 == 0) TS(56 + wg);
#pragma unroll
      for (int i = 0; i < 32; i++) acc0[i] = ((i & 2) ? gb1 : gb0) * acc0[i] + ((i & 2) ? g1 : g0) * az[i];
      wgmma_wait<0>();
      if (t128 == 0) TS(58 + wg);
      const uint32_t d23 = g2_buf(3) - g2_buf(5);
#pragma unroll
      for (int jb = 0; jb < 8; jb += 2) {
        uint32_t pk[4];
#pragma unroll
        for (int c = 0; c < 4; c++) {
          const int x = 4 * jb + 2 * c;
          const float gb = (c & 1) ? gb1 : gb0;
          pk[c] = pack_bf16(gb * ck[x] + acc0[x], gb * ck[x + 1] + acc0[x + 1]);
        }
        stmatrix_x4(srow + d23 + (((jb + (lane >> 4)) ^ (lane & 7)) << 4), pk[0], pk[1], pk[2], pk[3]);
      }
      fence_async_smem();
      __syncwarp();
      asm volatile(ELECT "cp.reduce.async.bulk.tensor.2d.global.shared::cta.add.bulk_group [%0, {%1, %2}], [%3];\n}"
                   ::"l"(&map_o), "r"(p * 64), "r"(orow), "r"(stg + d23) : "memory");
      bulk_commit();
      bulk_wait_read();
    }
    if (t128 == 0) TS(12 + wg);
    TS_END();
  } else if (warp < 12) {
    if (extra && kh) return;
    const int t128 = tid & 127, w4 = warp & 3;
    const unsigned e = __ldcg(&g_Sync[blockIdx.x * 32]) + 1;
    const int P = extra ? 0 : blockIdx.x;
    const int k1 = t128 >> 3, q = t128 & 7;
    const int t = 32 * w4 + 8 * (lane & 3) + (lane >> 2);
    const int u = t128 & 63, qh = t128 >> 6;
    const int krow = (P >> 3) + 128 * ((P >> 2) & 1) + 512 * (P & 3);
    const int gc0 = 2 * (lane & 3) + ((lane >> 2) & 1);
    uint2 ra[16], rb[16];
    {
      const int eo = (((krow + 64 * qh) * 257) >> 2) + u;
      const uint2* srcr = reinterpret_cast<const uint2*>(w_r) + eo;
      const uint2* srci = reinterpret_cast<const uint2*>(w_i) + eo;
#pragma unroll
      for (int i = 0; i < 16; i++) {
        const uint2* src = ((i & 2) ? srci : srcr) + ((i >> 2) * 4 + (i & 1) * 64) * 257;
        ra[i] = __ldg(src);
        rb[i] = make_uint2(0u, 0u);
        if (lane == 31) rb[i] = __ldg(src + 1);
      }
    }
    const uint4 gwa = __ldg(reinterpret_cast<const uint4*>(gate_w) + 8 * (lane >> 2) + gc0);
    const uint4 gwb = __ldg(reinterpret_cast<const uint4*>(gate_w) + 8 * (lane >> 2) + (gc0 ^ 1));
    if (!extra) {
      {
        const int ab = w4 & 1, cp = w4 >> 1;
        const int cc = 64 * (P >> 5) + 4 * (P & 15) + 2 * ab + ((P >> 4) & 1);
        const int fr = (cc == 0 && cp) ? 256 : cc, ph0 = (cp && cc) ? 128 : 0;
        const float amp = cc == 0 ? 0.5f : 1.0f;
        uint32_t pk[4];
#pragma unroll
        for (int i = 0; i < 4; i++) {
          const int d = 8 * lane + 2 * i;
          pk[i] = h2u(__floats2half2_rn(amp * __cosf((float)(((fr * d + ph0 + 256) & 511) - 256) * (3.14159265358979f / 256.0f)),
                                        amp * __cosf((float)(((fr * (d + 1) + ph0 + 256) & 511) - 256) * (3.14159265358979f / 256.0f))));
        }
        const int rl = 16 * ((P & 15) >> 2) + 2 * (P & 3) + cp + 8 * ab;
        __stcg(reinterpret_cast<uint4*>(g_T + (size_t)((P >> 4) * 4 + (lane >> 3)) * 8192 + rl * 128 + (((lane & 7) ^ (rl & 7)) << 4)),
               make_uint4(pk[0], pk[1], pk[2], pk[3]));
      }
      cluster_wait();
      mbar_arrive(BAR(B_TROW));
      const int par = krow & 1;
      uint32_t v0[16], v1[16], v2[16];
#pragma unroll
      for (int i = 0; i < 16; i++) {
        const uint32_t nx = __shfl_down_sync(0xffffffffu, ra[i].x, 1), ny = __shfl_down_sync(0xffffffffu, ra[i].y, 1);
        const uint32_t bx = lane == 31 ? rb[i].x : nx, by = lane == 31 ? rb[i].y : ny;
        v0[i] = (krow & 2) ? ra[i].y : ra[i].x;
        v1[i] = (krow & 2) ? bx : ra[i].y;
        v2[i] = (krow & 2) ? by : bx;
      }
      {
        const uint32_t mw = warp_max_exp(acc_max_exp(acc_max_exp(acc_max_exp(0u, v0), v1), v2));
        if (lane == 0) asm volatile("st.shared.b32 [%0], %1;" ::"r"(sb + OFF_TW2 + 448 + w4 * 4), "r"(mw) : "memory");
      }
      if (u == 63) {
        const uint32_t sn = par ? 0x4432u : 0x4410u;
#pragma unroll
        for (int i = 0; i < 16; i += 4)
          sts128(sb + OFF_TW2 + 256 + qh * 64 + i * 4, __byte_perm(v2[i], 0, sn), __byte_perm(v2[i + 1], 0, sn),
                 __byte_perm(v2[i + 2], 0, sn), __byte_perm(v2[i + 3], 0, sn));
      }
      if (par) {
#pragma unroll
        for (int i = 0; i < 16; i++) { const uint32_t ev = __byte_perm(v0[i], v1[i], 0x7632u); v1[i] = __byte_perm(v1[i], v2[i], 0x5410u); v0[i] = ev; }
      } else {
#pragma unroll
        for (int i = 0; i < 16; i++) { const uint32_t ev = __byte_perm(v0[i], v1[i], 0x5410u); v1[i] = __byte_perm(v0[i], v1[i], 0x7632u); v0[i] = ev; }
      }
      if (t128 == 0) TS(16);
      const uint32_t dst = sb + OFF_ST + (uint32_t)(32 * (u >> 4) + (u & 15)) * 128u;
      const uint32_t sw = (uint32_t)((qh * 4) ^ (u & 7));
      mbar_wait_u(BAR(B_TABFREE), 0);
#pragma unroll
      for (int i = 0; i < 16; i += 4) {
        sts128(dst + ((sw ^ (i >> 2)) << 4), v0[i], v0[i + 1], v0[i + 2], v0[i + 3]);
        sts128(dst + 2048 + ((sw ^ (i >> 2)) << 4), v1[i], v1[i + 1], v1[i + 2], v1[i + 3]);
      }
      fence_async_smem();
      mbar_arrive(BAR(B_WFULL));
      if (t128 == 0) TS(15);
      {
#pragma unroll 1
        for (int kk = 0; kk < 8; kk++) mbar_wait_u(BAR(B_XFULL + kk), 0);
        float d[4];
#pragma unroll
        for (int i = 0; i < 4; i++) {
          const int row = 4 * w4 + i;
          const uint32_t ad = sb + OFF_X + (lane >> 2) * 16384 + (uint32_t)(16 * j + row) * 128u + ((gc0 ^ (row & 7)) << 4);
          const uint4 xa = lds128(ad), xb = lds128(ad ^ 16);
          const uint32_t p0 = mul_bf16x2(xa.x, gwa.x), p1 = mul_bf16x2(xa.y, gwa.y), p2 = mul_bf16x2(xa.z, gwa.z), p3 = mul_bf16x2(xa.w, gwa.w);
          const uint32_t p4 = mul_bf16x2(xb.x, gwb.x), p5 = mul_bf16x2(xb.y, gwb.y), p6 = mul_bf16x2(xb.z, gwb.z), p7 = mul_bf16x2(xb.w, gwb.w);
          d[i] = (((bf_lo(p0) + bf_hi(p0)) + (bf_lo(p1) + bf_hi(p1))) + ((bf_lo(p2) + bf_hi(p2)) + (bf_lo(p3) + bf_hi(p3))))
               + (((bf_lo(p4) + bf_hi(p4)) + (bf_lo(p5) + bf_hi(p5))) + ((bf_lo(p6) + bf_hi(p6)) + (bf_lo(p7) + bf_hi(p7))));
        }
        float e0 = (lane & 1) ? d[1] : d[0], e1 = (lane & 1) ? d[3] : d[2];
        e0 += __shfl_xor_sync(0xffffffffu, (lane & 1) ? d[0] : d[1], 1);
        e1 += __shfl_xor_sync(0xffffffffu, (lane & 1) ? d[2] : d[3], 1);
        float f0 = (lane & 2) ? e1 : e0;
        f0 += __shfl_xor_sync(0xffffffffu, (lane & 2) ? e0 : e1, 2);
        f0 += __shfl_xor_sync(0xffffffffu, f0, 4);
        f0 += __shfl_xor_sync(0xffffffffu, f0, 8);
        f0 += __shfl_xor_sync(0xffffffffu, f0, 16);
        if (lane < 4) reinterpret_cast<float*>(smem + OFF_TW2 + 384)[4 * w4 + lane] = f0;
        __syncwarp();
        mbar_arrive_if(BAR(B_GDONE), lane == 0);
        if (t128 == 0) TS(60);
      }
    }
    asm volatile("setmaxnreg.inc.sync.aligned.u32 136;");
    __half2 tw1[16], tw2[16];
    float a1 = (float)t * (3.14159265358979f / 1024.0f), a2 = (float)q * (3.14159265358979f / 64.0f);
    asm volatile("" : "+f"(a1), "+f"(a2) :: "memory");
#pragma unroll
    for (int i = 1; i < 16; i++) {
      tw1[i] = __floats2half2_rn(__cosf(a1 * i), __sinf(a1 * i));
      tw2[i] = __floats2half2_rn(__cosf(a2 * i), __sinf(a2 * i));
    }
    if (extra) {
      if (t128 == 0) {
        mbar_init(BAR(B_YRDY), 1);
        poll_counter(&g_Fin[0], 16 * e);
        reinterpret_cast<volatile uint32_t*>(smem + OFF_EXP)[0] = poll_tagged(&g_Fin[1], e);
        mbar_expect_tx(BAR(B_YRDY), 16384);
        bulk_load(sb + OFF_FF, g_Y, 16384, BAR(B_YRDY));
      }
      bar_sync(2, 128);
    }
    mbar_wait_u(BAR(B_YRDY), 0);
    if (t128 == 0) TS(17);
    const uint32_t fbuf = sb + OFF_FF;
    const uint32_t x1 = (uint32_t)(k1 & 1) << 6;
    const uint32_t a_col = fbuf + (t ^ ((t >> 2) & 4)) * 8;
    const uint32_t a_row = fbuf + k1 * 1024 + x1 + q * 8;
    const uint32_t a_tr  = fbuf + k1 * 1024 + ((q * 64) ^ x1) + q * 8;
    C2 v[16];
    int ey;
    {
      uint32_t y[32];
      const uint32_t yl = fbuf + (uint32_t)(lane >> 3) * 512u + w4 * 128 + (lane & 7) * 16;
#pragma unroll
      for (int i = 0; i < 8; i++)
        asm volatile("ldmatrix.sync.aligned.m8n8.x4.shared.b16 {%0, %1, %2, %3}, [%4];"
                     : "=r"(y[4 * i]), "=r"(y[4 * i + 1]), "=r"(y[4 * i + 2]), "=r"(y[4 * i + 3]) : "r"(yl + i * 2048) : "memory");
      if (P == 0) {
#pragma unroll
        for (int n1 = 0; n1 < 16; n1++) {
          if (extra) { y[n1] = y[16 + n1] & 0xFFFFu; y[16 + n1] = 0; }
          else y[16 + n1] &= 0xFFFF0000u;
        }
      }
      const uint32_t my = warp_max_exp(acc_max_exp(0u, y));
      if (lane == 0) asm volatile("st.shared.b32 [%0], %1;" ::"r"(sb + OFF_TW2 + 464 + w4 * 4), "r"(my) : "memory");
      bar_sync(2, 128);
      const uint4 m1 = lds128(sb + OFF_TW2 + 464);
      ey = max((int)max(max(m1.x, m1.y), max(m1.z, m1.w)) - 12, 0);
      const uint32_t nby = ((uint32_t)(-(ey << 7)) & 0xFFFFu) * 0x10001u;
#pragma unroll
      for (int n1 = 0; n1 < 16; n1++) v[n1] = C2{u2h(bf2_to_h2(y[n1], nby)), u2h(bf2_to_h2(y[16 + n1], nby))};
    }
    if (t128 == 0) TS(18);
    fft16<-1>(v);
#pragma unroll
    for (int i = 1; i < 16; i++) v[i] = ctw<-1>(v[i], tw1[i]);
#pragma unroll
    for (int i = 0; i < 16; i++) sts_c2((a_col ^ ((i & 1) << 6)) + i * 1024, v[i]);
    bar_sync(2, 128);
    if (!extra) mbar_wait_u(BAR(B_WRDY), 0);
    if (t128 == 0) TS(23);
    uint32_t f[32];
    {
      const uint4* fsrc = g_W + (size_t)(extra ? 128 : P) * 1024 + t128;
#pragma unroll
      for (int i = 0; i < 8; i++) {
        const uint4 a = __ldcg(fsrc + i * 128);
        f[4 * i] = a.x; f[4 * i + 1] = a.y; f[4 * i + 2] = a.z; f[4 * i + 3] = a.w;
      }
    }
#pragma unroll
    for (int i = 0; i < 16; i++) v[i] = lds_c2((a_row ^ (((i & 1) << 6) | ((i & 2) << 4))) + (i >> 1) * 128);
    fft16<-1>(v);
#pragma unroll
    for (int i = 1; i < 16; i++) v[i] = ctw<-1>(v[i], tw2[i]);
    __syncwarp();
#pragma unroll
    for (int i = 0; i < 16; i++) sts_c2((a_row ^ (((i & 1) << 6) | ((i & 7) << 3))) + (i >> 1) * 128, v[i]);
    __syncwarp();
#pragma unroll
    for (int i = 0; i < 16; i++) v[i] = lds_c2((a_tr ^ ((i & 7) << 3)) + (i & 8) * 64);
    __half2 zs;
    {
      const uint32_t ex = ld_volatile_shared(sb + OFF_EXP);
      const int ew = max((int)(ex & 0xFFu) - 14, 0), eref = max((int)((ex >> 8) & 0xFFu) - 2, 0);
      const uint32_t nbw = ((uint32_t)(-(ew << 7)) & 0xFFFFu) * 0x10001u;
#pragma unroll
      for (int i = 0; i < 32; i++) f[i] = bf2_to_h2(f[i], nbw);
      zs = __float2half2_rn(__uint_as_float((uint32_t)max(127 + ey - eref, 1) << 23));
#pragma unroll
      for (int i = 1; i < 16; i++) tw1[i] = __hmul2(tw1[i], zs);
    }
    fft8<-1>(v);
    fft8<-1>(v + 8);
#pragma unroll
    for (int i = 0; i < 16; i++) v[i] = cmul<1>(v[i], u2h(f[2 * (i & ~1) + (i & 1)]), u2h(f[2 * (i & ~1) + 2 + (i & 1)]));
    fft8<1>(v);
    fft8<1>(v + 8);
    if (t128 == 0) TS(19);
#pragma unroll
    for (int i = 0; i < 16; i++) sts_c2((a_tr ^ ((i & 7) << 3)) + (i & 8) * 64, v[i]);
    __syncwarp();
#pragma unroll
    for (int i = 0; i < 16; i++) v[i] = lds_c2((a_row ^ (((i & 1) << 6) | ((i & 7) << 3))) + (i >> 1) * 128);
#pragma unroll
    for (int i = 1; i < 16; i++) v[i] = ctw<1>(v[i], tw2[i]);
    fft16<1>(v);
    __syncwarp();
#pragma unroll
    for (int i = 0; i < 16; i++) sts_c2((a_row ^ (((i & 1) << 6) | ((i & 2) << 4))) + (i >> 1) * 128, v[i]);
    bar_sync(2, 128);
#pragma unroll
    for (int i = 0; i < 16; i++) v[i] = lds_c2((a_col ^ ((i & 1) << 6)) + i * 1024);
    v[0] = C2{__hmul2(v[0].x, zs), __hmul2(v[0].y, zs)};
#pragma unroll
    for (int i = 1; i < 16; i++) v[i] = ctw<1>(v[i], tw1[i]);
    fft16<1>(v);
    bar_sync(2, 128);
    {
      const uint32_t zst = fbuf + (uint32_t)(((lane >> 3) & 1) * 2 + (lane & 1)) * 4160u
                         + (uint32_t)(128 * (lane >> 4) + 32 * w4 + 8 * ((lane >> 1) & 3)) * 2u;
#pragma unroll
      for (int n1 = 0; n1 < 16; n1 += 2)
        asm volatile("stmatrix.sync.aligned.m8n8.x4.trans.shared.b16 [%0], {%1, %2, %3, %4};"
                     ::"r"(zst + n1 * 256), "r"(h2u(v[n1].x)), "r"(h2u(v[n1].y)), "r"(h2u(v[n1 + 1].x)), "r"(h2u(v[n1 + 1].y)) : "memory");
    }
    fence_async_smem();
    bar_sync(2, 128);
    bool zlast = false;
    if (t128 == 0) {
      TS(20);
      uint16_t* zrow = g_Z + (size_t)(16 * (P >> 2) + 2 * (P & 3)) * 2048;
      if (extra) {
        bulk_store(zrow + 2048, fbuf, 4096);
      } else {
#pragma unroll 1
        for (int c = 0; c < 16384; c += Z_PIECE) {
          const int row = c >> 12, o = c & 4095;
          if (P != 0 || row != 2) bulk_store(zrow + ((row & 1) * 8 + (row >> 1)) * 2048 + (o >> 1), fbuf + row * 4160 + o, Z_PIECE);
          bulk_commit();
          bulk_wait_read();
        }
      }
      bulk_commit();
      bulk_wait_all();
      if (extra) g_Sync[blockIdx.x * 32] = e;
    }
    zlast = __shfl_sync(0xffffffffu, zlast, 0);
    if (t128 < 16) red_relaxed(&g_Rdy[(2 * t128 + ((P >> 4) & 1)) * 32 + 14 + (P >> 5)]);
    if (t128 == 0) TS(21);
    if (!extra) TS_END();
  } else {
    asm volatile("setmaxnreg.dec.sync.aligned.u32 40;");
    if (extra) return;
    if (warp == 12) {
      cluster_wait();
      const CUtensorMap* wm = kh ? &map_wu : &map_wg;
      const CUtensorMap* wn = kh ? &map_un : &map_gn;
      mbar_wait_u(BAR(B_XFULL + W_GATE), 0);
#pragma unroll 1
      for (int n = 0; n < 28; n++) {
        const int tile = n >> 3, slot = n & 3;
        int c0 = g1_chunk(j, tile) * 64 + (tile == 3 ? (j & 1) * 32 : 0), c1 = (n & 7) * (tile == 3 ? 128 : 64);
        uint32_t full = BAR(B_RFULL + ((tile & 1) ^ 1) * 4 + slot), dst = sb + OFF_R + slot * 16384 + kh * 8192;
        const CUtensorMap* m = tile == 3 ? wn : wm;
        if (n == 16) asm volatile("prefetch.tensormap [%0];" ::"l"(wn) : "memory");
        asm volatile("" : "+r"(c0), "+r"(c1), "+r"(full), "+r"(dst), "+l"(m));
        mbar_wait_u(BAR(B_REMPTY + slot), ((n >> 2) & 1) ^ 1);
        mbar_expect_tx_e(full, 16384);
        tma2d_mc_e(dst, m, c0, c1, full);
        TSP(64 + n, lane == 0);
      }
    } else if (warp == 13) {
      bar_arrive(6, 64);
      cluster_wait();
      {
        const unsigned e = __ldcg(&g_Sync[blockIdx.x * 32]) + 1;
        const int wl = ((int)blockIdx.x & 7) * 16 + ((int)blockIdx.x >> 3);
        mbar_wait_u(BAR(B_TROW), 0);
        asm volatile("fence.acq_rel.gpu;" ::: "memory");
        uint32_t mx = 0;
#pragma unroll 1
        for (int kk = 0; kk < 8; kk++) {
          mbar_wait_u(BAR(B_XFULL + kk), 0);
#pragma unroll
          for (int i = 0; i < 4; i++) {
            const uint4 xa = lds128(sb + OFF_X + kk * 16384 + j * 2048 + i * 512 + lane * 16);
            const uint32_t xw[4] = {xa.x, xa.y, xa.z, xa.w};
            mx = acc_max_exp(mx, xw);
          }
        }
        mx = warp_max_exp(mx);
        mbar_wait_u(BAR(B_WFULL), 0);
        const uint4 m4 = lds128(sb + OFF_TW2 + 448);
        unsigned long long* gmax = reinterpret_cast<unsigned long long*>(&g_Sync[17 * 32 + 2]) + (lane & 1);
        unsigned long long tag = ((unsigned long long)e << 8) | ((lane & 1) ? mx : max(max(m4.x, m4.y), max(m4.z, m4.w))), prevm = 0;
        asm volatile("{\n.reg .pred p;\nsetp.lt.u32 p, %3, 2;\n@p atom.relaxed.gpu.global.max.u64 %0, [%1], %2;\n}"
                     : "+l"(prevm) : "l"(gmax), "l"(tag), "r"(lane) : "memory");
        asm volatile(ELECT "cp.async.bulk.global.shared::cta.bulk_group [%0], [%1], 128;\n}"
                     ::"l"(g_W + ((size_t)128 * 128 + wl) * 8), "r"(sb + OFF_TW2 + 256) : "memory");
#pragma unroll 1
        for (int c = 0; c < 4; c++) {
          asm volatile(ELECT "cp.async.bulk.tensor.2d.global.shared::cta.bulk_group [%0, {%1, %2}], [%3];\n}"
                       ::"l"(&map_w), "r"(wl * 64), "r"(c * 32), "r"(sb + OFF_ST + c * 4096) : "memory");
          bulk_commit();
          bulk_wait_read();
        }
        mbar_arrive_if(BAR(B_STEMPTY + 1), lane == 0);
        bulk_wait_all();
        __syncwarp();
        unsigned old = 0;
        const bool go = __all_sync(0xffffffffu, (unsigned)(prevm >> 32) != 0xFFFFFFFFu) && lane == 0;
        asm volatile("{\n.reg .pred p;\nsetp.ne.u32 p, %2, 0;\n@p atom.relaxed.gpu.global.add.u32 %0, [%1], 1;\n}"
                     : "+r"(old) : "l"(&g_Sync[16 * 32 + 1]), "r"((uint32_t)go) : "memory");
        old = __shfl_sync(0xffffffffu, old, 0);
        if (old + 1 == 128 * e) {
          const unsigned mv = ld_relaxed(reinterpret_cast<const unsigned*>(gmax)) & 0xFFu;
          const unsigned pay = (e << 16) | (__shfl_sync(0xffffffffu, mv, 1) << 8) | __shfl_sync(0xffffffffu, mv, 0);
          asm volatile("{\n.reg .pred p;\nsetp.lt.u32 p, %2, 16;\n@p st.relaxed.gpu.global.u32 [%0], %1;\n}"
                       ::"l"(&g_Fin[(lane & 15) * 32 + 1]), "r"(pay), "r"(lane) : "memory");
        }
        TSP(22, lane == 0);
      }
      {
        sts128(sb + OFF_ZERO + lane * 16, 0u, 0u, 0u, 0u);
        sts128(sb + OFF_ZERO + 512 + lane * 16, 0u, 0u, 0u, 0u);
        fence_async_smem();
        __syncwarp();
        const __nv_bfloat16* orow = out + (size_t)(r * 128 + 16 * j) * 512;
#pragma unroll 1
        for (int i = 0; i < 16; i++) {
          asm volatile(ELECT "cp.async.bulk.global.shared::cta.bulk_group [%0], [%1], 1024;\n}"
                       ::"l"(orow + i * 512), "r"(sb + OFF_ZERO) : "memory");
          if (i & 1) { bulk_commit(); bulk_wait_read(); }
        }
        bulk_wait_all();
        __syncwarp();
      }
      {
        mbar_wait_u(BAR(B_GDONE), 0);
        const float logit = reinterpret_cast<const float*>(smem + OFF_TW2 + 384)[lane & 15];
        const float gv = __fdividef(1.0f, 1.0f + __expf(-logit));
        asm volatile("{\n.reg .pred p;\nsetp.lt.u32 p, %2, 16;\n@p st.global.cg.f32 [%0], %1;\n}"
                     ::"l"(&g_G[r * 128 + 16 * j + (lane & 15)]), "f"(gv), "r"(lane) : "memory");
        __syncwarp();
        asm volatile("{\n.reg .pred p;\nsetp.lt.u32 p, %1, 2;\n@p red.release.gpu.global.add.u32 [%0], 1;\n}"
                     ::"l"(&g_Rdy[(2 * r + (lane & 1)) * 32 + 18]), "r"(lane) : "memory");
      }
      uint32_t ready = 0;
      const int n0 = p * 64 + kh * 256;
#define WAIT_READY(i) do { uint32_t n_ = 0;                                                \
        while (!((ready >> (i)) & 1)) {                                                      \
          ready = __shfl_sync(0xffffffffu, ld_volatile_shared(sb + OFF_READY), 0);           \
          if (++n_ > (SPIN_LIMIT << 4)) __trap();                                            \
        } } while (0)
#pragma unroll 1
      for (int i = 0; i < 14; i++) {
        const int chunk = g2_chunk(kq, i);
        const uint32_t b = g2_seq(i) & 7u, ph = g2_seq(i) >> 3;
        uint32_t buf = sb + g2_buf(b), full = BAR(B_G2FULL + b);
        int c1 = chunk * 64;
        if (i == 10) {
          asm volatile("prefetch.tensormap [%0];" ::"l"(&map_z) : "memory");
          asm volatile("prefetch.tensormap [%0];" ::"l"(&map_o) : "memory");
        }
        const uint8_t* src = g_H + (size_t)(r * 28 + chunk) * 16384;
        asm volatile("" : "+r"(c1), "+r"(full), "+r"(buf), "+l"(src));
        mbar_wait_u(BAR(B_G2EMPTY + b), ph);
        mbar_expect_tx_e(full, 32768);
        tma2d_mc_e(buf + 16384 + kh * 8192, &map_wd, n0, c1, full);
        WAIT_READY(i);
        bulk_load_e(buf, src, 16384, full);
        TSP(32 + i, lane == 0);
      }
      int nb = 0, nz = 0;
      uint32_t spins = 0;
#pragma unroll 1
      while (nz < 4) {
        const int bb = (0x0435 >> (4 * nb)) & 7;
        if (nb < 4 && __all_sync(0xffffffffu, mbar_test(BAR(B_G2EMPTY + bb), nb == 0 || nb == 3))) {
          mbar_expect_tx_e(BAR(B_G2FULL + bb), 24576);
          bulk_load_e(sb + g2_buf(bb) + 16384, g_T + (size_t)((2 * nb + kq) * 4 + p) * 8192, 8192, BAR(B_G2FULL + bb));
          nb++;
        }
        ready = __shfl_sync(0xffffffffu, ld_volatile_shared(sb + OFF_READY), 0);
        while (nz < nb && ((ready >> (14 + nz)) & 1)) {
          const int bz = (0x0435 >> (4 * nz)) & 7;
          const uint32_t buf = sb + g2_buf(bz), full = BAR(B_G2FULL + bz);
          tma2d_e(buf, &map_z, r * 128, (2 * nz + kq) * 64, full);
          tma2d_e(buf + 8192, &map_z, r * 128 + 64, (2 * nz + kq) * 64, full);
          TSP(46 + nz, lane == 0);
          nz++;
        }
        if (++spins > (SPIN_LIMIT << 4)) __trap();
      }
    } else if (warp == 14) {
      if (lane == 0) {
        asm volatile("prefetch.tensormap [%0];" ::"l"(&map_w) : "memory");
        asm volatile("prefetch.tensormap [%0];" ::"l"(&map_y) : "memory");
        asm volatile("prefetch.tensormap [%0];" ::"l"(&map_wd) : "memory");
        asm volatile("prefetch.tensormap [%0];" ::"l"(&map_z) : "memory");
      }
      __syncwarp();
      const unsigned e = __ldcg(&g_Sync[blockIdx.x * 32]) + 1;
      cluster_wait();
      if (lane == 0) {
        mbar_wait(BAR(B_STFULL + 0), 0);
#pragma unroll 1
        for (int q = 0; q < 4; q++) {
          tma2d_store(&map_y, r * 256 + q * 64, j * 32, sb + OFF_FF + q * 4096);
          if ((q & Y_PACE) == Y_PACE) { bulk_commit(); bulk_wait_read(); }
        }
        mbar_arrive(BAR(B_FFFREE));
        bulk_wait_all();
        red_relaxed(&g_Fin[2 * j * 32]); red_relaxed(&g_Fin[(2 * j + 1) * 32]);
        TS(24);
#pragma unroll 1
        for (int ev = 1; ev < 5; ev++) {
          const int chunk = g1_chunk(j, ev - 1);
          uint8_t* dst = g_H + (size_t)(r * 28 + chunk) * 16384 + (ev == 4 ? (j & 1) * 8192 : 0);
          const uint32_t src = sb + (ev == 4 ? OFF_NST : OFF_ST);
          const int piece = ev < 3 ? ST_PIECE : LATE_PIECE;
          mbar_wait(BAR(B_STFULL + ev), 0);
          if (ev == 3) TS(50);
#pragma unroll 1
          for (int q = 0; q < (ev == 4 ? 8192 : 16384); q += piece) {
            bulk_store(dst + q, src + q, piece);
            bulk_commit();
            bulk_wait_read();
          }
          if (ev == 3) TS(51);
          if (ev < 4) mbar_arrive(BAR(B_STEMPTY + 1 + ev));
          else { mbar_arrive(BAR(B_G2EMPTY + 5)); mbar_arrive_remote_light(mapa(BAR(B_G2EMPTY + 5), kh ^ 1)); }
          bulk_wait_all();
          red_relaxed(&g_Rdy[ev == 4 ? (2 * r + (j >> 2)) * 32 + 10 + ((j >> 1) & 1)
                                     : (2 * r + (j & 1)) * 32 + 4 * ev - 4 + (j >> 1) + ((ev == 3 && j >= 4) ? 2 : 0)]);
          TS(24 + ev);
        }
      }
    } else {
      const unsigned e = __ldcg(&g_Sync[blockIdx.x * 32]) + 1;
      bar_sync(6, 64);
      cluster_wait();
      if (lane == 0) {
        const CUtensorMap* wm = kh ? &map_wu : &map_wg;
        const int c1 = (r >> 1) * 64;
        mbar_wait(BAR(B_XFULL + 7), 0);
        tma2d_prefetch(wm, g1_chunk(j, 1) * 64, c1);
        mbar_wait(BAR(B_TABFREE), 0);
        tma2d_prefetch(wm, g1_chunk(j, 2) * 64, c1);
        mbar_wait(BAR(B_STFULL + 0), 0);
        mbar_expect_tx(BAR(B_YRDY), 16384);
        mbar_wait(BAR(B_FFFREE), 0);
        poll_counter(&g_Fin[((int)blockIdx.x >> 3) * 32], 16 * e);
        bulk_load(sb + OFF_FF, g_Y + (size_t)blockIdx.x * 4096, 16384, BAR(B_YRDY));
        TS(31);
        tma2d_prefetch(wm, g1_chunk(j, 3) * 64, c1);
        reinterpret_cast<volatile uint32_t*>(smem + OFF_EXP)[0] = poll_tagged(&g_Fin[((int)blockIdx.x >> 3) * 32 + 1], e);
        mbar_arrive(BAR(B_WRDY));
        bulk_prefetch(wd_ptr + (size_t)blockIdx.x * 7168, 14336);
      }
      __syncwarp();
      const int i = lane < 19 ? lane : 0;
      bool gload = false;
      const unsigned target = ((i == 10 || i == 11) ? 2 : i == 18 ? 8 : i < 14 ? 1 : (i == 14 && kq == 0) ? 17 : 16) * e;
      const unsigned* cptr = &g_Rdy[(2 * r + kq) * 32 + i];
      uint32_t ready = 0, n = 0;
      unsigned pv[NPOLL];
#pragma unroll
      for (int c = 0; c < NPOLL; c++) pv[c] = ld_relaxed(cptr);
      while (ready != 0xffffffffu) {
#pragma unroll
        for (int c = 0; c < NPOLL; c++) {
          ready |= __ballot_sync(0xffffffffu, (int)(pv[c] - target) >= 0);
          if (!((ready >> lane) & 1)) pv[c] = ld_relaxed(cptr);
          if (lane == 0) asm volatile("st.volatile.shared.b32 [%0], %1;" ::"r"(sb + OFF_READY), "r"(ready) : "memory");
        }
        if (++n > SPIN_LIMIT) __trap();
        if (!gload && (ready & 0x40000u)) {
          gload = true;
          reinterpret_cast<float4*>(smem + OFF_G)[lane] = __ldcg(reinterpret_cast<const float4*>(g_G + r * 128) + lane);
          mbar_arrive(BAR(B_GFULL));
        }
      }
      if (lane == 0) g_Sync[blockIdx.x * 32] = e;
    }
    TS_END();
  }
#undef BAR
}

typedef CUresult (*EncodeFn)(CUtensorMap*, CUtensorMapDataType, cuuint32_t, void*, const cuuint64_t*, const cuuint64_t*,
                             const cuuint32_t*, const cuuint32_t*, CUtensorMapInterleave, CUtensorMapSwizzle,
                             CUtensorMapL2promotion, CUtensorMapFloatOOBfill);

void make_map(EncodeFn enc, CUtensorMap* m, const void* ptr, uint64_t inner, uint64_t outer, uint32_t box_outer,
              uint32_t box_inner = 64) {
  cuuint64_t dims[2] = {inner, outer};
  cuuint64_t strides[1] = {inner * 2};
  cuuint32_t box[2] = {box_inner, box_outer};
  cuuint32_t es[2] = {1, 1};
  enc(m, CU_TENSOR_MAP_DATA_TYPE_BFLOAT16, 2, const_cast<void*>(ptr), dims, strides, box, es, CU_TENSOR_MAP_INTERLEAVE_NONE,
      box_inner == 64 ? CU_TENSOR_MAP_SWIZZLE_128B : CU_TENSOR_MAP_SWIZZLE_64B, CU_TENSOR_MAP_L2_PROMOTION_L2_128B, CU_TENSOR_MAP_FLOAT_OOB_FILL_NONE);
}

}

extern "C" void kernel_launch(void* const* d_in, const int* in_sizes, int n_in, void* d_out, int out_size) {
  static EncodeFn enc = nullptr;
  if (!enc) {
    void* fn = nullptr;
    cudaDriverEntryPointQueryResult q;
    cudaGetDriverEntryPoint("cuTensorMapEncodeTiled", &fn, cudaEnableDefault, &q);
    enc = (EncodeFn)fn;
    cudaFuncSetAttribute(fused_kernel, cudaFuncAttributeMaxDynamicSharedMemorySize, SMEM_BYTES);
  }
  const __nv_bfloat16* x  = (const __nv_bfloat16*)d_in[0];
  const __nv_bfloat16* wr = (const __nv_bfloat16*)d_in[1];
  const __nv_bfloat16* wi = (const __nv_bfloat16*)d_in[2];
  const __nv_bfloat16* wg = (const __nv_bfloat16*)d_in[4];
  const __nv_bfloat16* wu = (const __nv_bfloat16*)d_in[5];
  const __nv_bfloat16* wd = (const __nv_bfloat16*)d_in[6];
  const __nv_bfloat16* gw = (const __nv_bfloat16*)d_in[7];
  void *yp = nullptr, *zp = nullptr, *wp = nullptr;
  cudaGetSymbolAddress(&wp, g_W);
  cudaGetSymbolAddress(&yp, g_Y);
  cudaGetSymbolAddress(&zp, g_Z);
  CUtensorMap mx, mg, mu, md, my, mz, mw, mgn, mun, mo;
  make_map(enc, &mo, d_out, 512, 2048, 16);
  make_map(enc, &mgn, wg, 1792, 512, 128, 32);
  make_map(enc, &mun, wu, 1792, 512, 128, 32);
  make_map(enc, &mw, wp, 8192, 128, 32);
  make_map(enc, &my, yp, 4096, 256, 32);
  make_map(enc, &mz, zp, 2048, 512, 64);
  make_map(enc, &mx, x, 512, 2048, 128);
  make_map(enc, &mg, wg, 1792, 512, 64);
  make_map(enc, &mu, wu, 1792, 512, 64);
  make_map(enc, &md, wd, 512, 1792, 64);
  fused_kernel<<<130, 512, SMEM_BYTES>>>(mx, mg, mu, md, my, mz, mw, mgn, mun, mo, x, wr, wi, wd, gw, (__nv_bfloat16*)d_out);
}
```

```cpp
#include <cuda_runtime.h>
#include <cuda_bf16.h>
#include <cuda_fp16.h>
#include <cuda.h>
#include <stdint.h>

#define LD_GATE 6
namespace {

constexpr uint32_t OFF_X   = 0;
constexpr uint32_t OFF_R   = 131072;
constexpr uint32_t OFF_ST  = 196608;
constexpr uint32_t OFF_FF  = 212992;
constexpr uint32_t OFF_NST = OFF_R + 32768;
constexpr uint32_t OFF_TW2 = 229376;
constexpr uint32_t OFF_G   = 230400;
constexpr uint32_t OFF_ZERO = OFF_G - 512;
constexpr uint32_t OFF_BAR = 230912;
constexpr uint32_t SMEM_BYTES = 231424;

enum : uint32_t {
  B_XFULL = 0, B_RFULL = 8, B_REMPTY = 16, B_G2FULL = 20, B_G2EMPTY = 26, B_STFULL = 32, B_STEMPTY = 37,
  B_GFULL = 42, B_GDONE = 43, B_FFFREE = 44, B_WFULL = 45, B_TABFREE = 46, B_YRDY = 47, B_WRDY = 48, B_HDONE = 49,
  B_ZFULL = 50, B_FFDONE = 54, B_FFTOUT = 55, B_YMAX = 56, B_ZPUB = 57, B_COUNT = 58
};
constexpr uint32_t OFF_READY = OFF_TW2 + 496;
constexpr uint32_t OFF_EXP = OFF_READY + 4;

__device__ __align__(1024) uint32_t g_Y[256 * 2048];
__device__ __align__(1024) uint8_t g_H[16 * 28 * 16384];
__device__ __align__(1024) uint16_t g_Z[512 * 2048];
__device__ __align__(1024) uint8_t g_T[8 * 4 * 8192];
__device__ __align__(128) float g_G[2048];
__device__ __align__(1024) uint4 g_W[129 * 128 * 8];
__device__ __align__(128) unsigned g_Sync[130 * 32];
__device__ __align__(128) unsigned g_Rdy[32 * 32];
__device__ __align__(128) unsigned g_Fin[16 * 32];

__device__ __forceinline__ uint32_t smem_u32(const void* p) { return (uint32_t)__cvta_generic_to_shared(p); }
__device__ __forceinline__ void mbar_init(uint32_t bar, uint32_t cnt) {
  asm volatile("mbarrier.init.shared::cta.b64 [%0], %1;" ::"r"(bar), "r"(cnt) : "memory");
}
__device__ __forceinline__ void mbar_expect_tx(uint32_t bar, uint32_t bytes) {
  asm volatile("mbarrier.arrive.expect_tx.shared::cta.b64 _, [%0], %1;" ::"r"(bar), "r"(bytes) : "memory");
}
__device__ __forceinline__ void mbar_arrive(uint32_t bar) {
  asm volatile("mbarrier.arrive.shared::cta.b64 _, [%0];" ::"r"(bar) : "memory");
}
__device__ __forceinline__ void mbar_arrive_if(uint32_t bar, bool pred) {
  asm volatile("{\n.reg .pred p;\nsetp.ne.u32 p, %1, 0;\n@p mbarrier.arrive.shared::cta.b64 _, [%0];\n}" ::"r"(bar), "r"((uint32_t)pred) : "memory");
}
__device__ __forceinline__ void mbar_arrive_remote_if(uint32_t bar, bool pred) {
  asm volatile("{\n.reg .pred p;\nsetp.ne.u32 p, %1, 0;\n@p mbarrier.arrive.shared::cluster.b64 _, [%0];\n}" ::"r"(bar), "r"((uint32_t)pred) : "memory");
}
__device__ __forceinline__ uint32_t mapa(uint32_t addr, uint32_t cta) {
  uint32_t r;
  asm volatile("mapa.shared::cluster.u32 %0, %1, %2;" : "=r"(r) : "r"(addr), "r"(cta));
  return r;
}
__device__ __forceinline__ bool mbar_try(uint32_t bar, uint32_t parity) {
  uint32_t ok;
  asm volatile("{\n.reg .pred p;\nmbarrier.try_wait.parity.shared::cta.b64 p, [%1], %2;\nselp.u32 %0, 1, 0, p;\n}"
               : "=r"(ok) : "r"(bar), "r"(parity) : "memory");
  return ok != 0;
}
constexpr uint32_t SPIN_LIMIT = 1u << 20;
__device__ __forceinline__ void mbar_wait(uint32_t bar, uint32_t parity) {
  uint32_t n = 0;
  while (!mbar_try(bar, parity)) { if (++n > SPIN_LIMIT) __trap(); }
}
__device__ __forceinline__ void mbar_wait_u(uint32_t bar, uint32_t parity) {
  uint32_t n = 0;
  while (!__all_sync(0xffffffffu, mbar_try(bar, parity))) { if (++n > SPIN_LIMIT) __trap(); }
}
__device__ __forceinline__ void bulk_load(uint32_t dst, const void* src, uint32_t bytes, uint32_t bar) {
  asm volatile("cp.async.bulk.shared::cluster.global.mbarrier::complete_tx::bytes [%0], [%1], %2, [%3];"
               ::"r"(dst), "l"(src), "r"(bytes), "r"(bar) : "memory");
}
#define ELECT "{\n.reg .pred e;\nelect.sync _|e, 0xffffffff;\n@e "
__device__ __forceinline__ void mbar_expect_tx_e(uint32_t bar, uint32_t bytes) {
  asm volatile(ELECT "mbarrier.arrive.expect_tx.shared::cta.b64 _, [%0], %1;\n}" ::"r"(bar), "r"(bytes) : "memory");
}
__device__ __forceinline__ void tma2d_e(uint32_t dst, const CUtensorMap* m, int c0, int c1, uint32_t bar) {
  asm volatile(ELECT "cp.async.bulk.tensor.2d.shared::cluster.global.mbarrier::complete_tx::bytes [%0], [%1, {%3, %4}], [%2];\n}"
               ::"r"(dst), "l"(m), "r"(bar), "r"(c0), "r"(c1) : "memory");
}
__device__ __forceinline__ void tma2d_mc_e(uint32_t dst, const CUtensorMap* m, int c0, int c1, uint32_t bar) {
  asm volatile(ELECT "cp.async.bulk.tensor.2d.shared::cluster.global.mbarrier::complete_tx::bytes.multicast::cluster [%0], [%1, {%3, %4}], [%2], %5;\n}"
               ::"r"(dst), "l"(m), "r"(bar), "r"(c0), "r"(c1), "h"((uint16_t)3) : "memory");
}
__device__ __forceinline__ void bulk_load_e(uint32_t dst, const void* src, uint32_t bytes, uint32_t bar) {
  asm volatile(ELECT "cp.async.bulk.shared::cluster.global.mbarrier::complete_tx::bytes [%0], [%1], %2, [%3];\n}"
               ::"r"(dst), "l"(src), "r"(bytes), "r"(bar) : "memory");
}
__device__ __forceinline__ void bulk_store(void* dst, uint32_t src, uint32_t bytes) {
  asm volatile("cp.async.bulk.global.shared::cta.bulk_group [%0], [%1], %2;" ::"l"(dst), "r"(src), "r"(bytes) : "memory");
}
__device__ __forceinline__ void tma2d_store(const CUtensorMap* m, int c0, int c1, uint32_t src) {
  asm volatile("cp.async.bulk.tensor.2d.global.shared::cta.bulk_group [%0, {%1, %2}], [%3];"
               ::"l"(m), "r"(c0), "r"(c1), "r"(src) : "memory");
}
__device__ __forceinline__ void tma2d_prefetch(const CUtensorMap* m, int c0, int c1) {
  asm volatile("cp.async.bulk.prefetch.tensor.2d.L2.global [%0, {%1, %2}];" ::"l"(m), "r"(c0), "r"(c1) : "memory");
}
__device__ __forceinline__ void bulk_commit() { asm volatile("cp.async.bulk.commit_group;" ::: "memory"); }
__device__ __forceinline__ void bulk_wait_read() { asm volatile("cp.async.bulk.wait_group.read 0;" ::: "memory"); }
__device__ __forceinline__ void bulk_wait_done() { asm volatile("cp.async.bulk.wait_group 0;" ::: "memory"); }
__device__ __forceinline__ void bulk_wait_all() {
  asm volatile("cp.async.bulk.wait_group 0;" ::: "memory");
  asm volatile("fence.acq_rel.gpu;" ::: "memory");
}
__device__ __forceinline__ void cluster_arrive() { asm volatile("barrier.cluster.arrive.relaxed.aligned;" ::: "memory"); }
__device__ __forceinline__ void cluster_wait() { asm volatile("barrier.cluster.wait.acquire.aligned;" ::: "memory"); }
__device__ __forceinline__ uint32_t ld_volatile_shared(uint32_t addr) {
  uint32_t v;
  asm volatile("ld.volatile.shared.b32 %0, [%1];" : "=r"(v) : "r"(addr) : "memory");
  return v;
}
__device__ __forceinline__ unsigned ld_relaxed(const unsigned* p) {
  unsigned v;
  asm volatile("ld.relaxed.gpu.global.u32 %0, [%1];" : "=r"(v) : "l"(p) : "memory");
  return v;
}
__device__ __forceinline__ void bulk_prefetch(const void* src, uint32_t bytes) {
  asm volatile("cp.async.bulk.prefetch.L2.global [%0], %1;" ::"l"(src), "r"(bytes) : "memory");
}
__device__ __forceinline__ void fence_async_smem() { asm volatile("fence.proxy.async.shared::cta;" ::: "memory"); }
__device__ __forceinline__ void red_relaxed(unsigned* p) {
  asm volatile("red.relaxed.gpu.global.add.u32 [%0], 1;" ::"l"(p) : "memory");
}
__device__ __forceinline__ void poll_counter(const unsigned* p, unsigned target) {
  uint32_t n = 0;
  while ((int)(ld_relaxed(p) - target) < 0) { if (++n > SPIN_LIMIT) __trap(); }
}
__device__ __forceinline__ void bar_sync(int id, int n) { asm volatile("bar.sync %0, %1;" ::"r"(id), "r"(n) : "memory"); }
__device__ __forceinline__ void bar_arrive(int id, int n) { asm volatile("bar.arrive %0, %1;" ::"r"(id), "r"(n) : "memory"); }
__device__ __forceinline__ void wgmma_fence() { asm volatile("wgmma.fence.sync.aligned;" ::: "memory"); }
__device__ __forceinline__ void wgmma_commit() { asm volatile("wgmma.commit_group.sync.aligned;" ::: "memory"); }
template <int N> __device__ __forceinline__ void wgmma_wait() { asm volatile("wgmma.wait_group.sync.aligned %0;" ::"n"(N) : "memory"); }
constexpr uint32_t HI128 = 0x40000040u, HI64 = 0x80000020u;
__device__ __forceinline__ uint32_t desc_k(uint32_t addr) { return ((addr & 0x3FFFF) >> 4) | (1u << 16); }
__device__ __forceinline__ uint32_t desc_mn(uint32_t addr) { return ((addr & 0x3FFFF) >> 4) | (512u << 16); }
template <int TA, int TB, int SA = 1>
__device__ __forceinline__ void wgmma_n128(float (&d)[64], uint32_t da, uint32_t db, int scale_d, uint32_t ahi = HI128) {
  asm volatile(
      "{\n.reg .pred p;\n.reg .b64 da, db;\nsetp.ne.b32 p, %66, 0;\n"
      "mov.b64 da, {%64, %70};\nmov.b64 db, {%65, 0x40000040};\n"
      "wgmma.mma_async.sync.aligned.m64n128k16.f32.bf16.bf16 "
      "{%0, %1, %2, %3, %4, %5, %6, %7, %8, %9, %10, %11, %12, %13, %14, %15, %16, %17, %18, %19, %20, %21, %22, %23, %24, %25, %26, %27, %28, %29, %30, %31, %32, %33, %34, %35, %36, %37, %38, %39, %40, %41, %42, %43, %44, %45, %46, %47, %48, %49, %50, %51, %52, %53, %54, %55, %56, %57, %58, %59, %60, %61, %62, %63}, "
      "da, db, p, %69, 1, %67, %68;\n}\n"
      :
      "+f"(d[0]), "+f"(d[1]), "+f"(d[2]), "+f"(d[3]), "+f"(d[4]), "+f"(d[5]), "+f"(d[6]), "+f"(d[7]),
      "+f"(d[8]), "+f"(d[9]), "+f"(d[10]), "+f"(d[11]), "+f"(d[12]), "+f"(d[13]), "+f"(d[14]), "+f"(d[15]),
      "+f"(d[16]), "+f"(d[17]), "+f"(d[18]), "+f"(d[19]), "+f"(d[20]), "+f"(d[21]), "+f"(d[22]), "+f"(d[23]),
      "+f"(d[24]), "+f"(d[25]), "+f"(d[26]), "+f"(d[27]), "+f"(d[28]), "+f"(d[29]), "+f"(d[30]), "+f"(d[31]),
      "+f"(d[32]), "+f"(d[33]), "+f"(d[34]), "+f"(d[35]), "+f"(d[36]), "+f"(d[37]), "+f"(d[38]), "+f"(d[39]),
      "+f"(d[40]), "+f"(d[41]), "+f"(d[42]), "+f"(d[43]), "+f"(d[44]), "+f"(d[45]), "+f"(d[46]), "+f"(d[47]),
      "+f"(d[48]), "+f"(d[49]), "+f"(d[50]), "+f"(d[51]), "+f"(d[52]), "+f"(d[53]), "+f"(d[54]), "+f"(d[55]),
      "+f"(d[56]), "+f"(d[57]), "+f"(d[58]), "+f"(d[59]), "+f"(d[60]), "+f"(d[61]), "+f"(d[62]), "+f"(d[63])
      : "r"(da), "r"(db), "r"(scale_d), "n"(TA), "n"(TB), "n"(SA), "r"(ahi));
}
template <uint32_t AHI>
__device__ __forceinline__ void wgmma_n64_bf(float (&d)[32], uint32_t da, uint32_t db, int scale_d) {
  asm volatile(
      "{\n.reg .pred p;\n.reg .b64 da, db;\nsetp.ne.b32 p, %34, 0;\n"
      "mov.b64 da, {%32, %35};\nmov.b64 db, {%33, 0x40000040};\n"
      "wgmma.mma_async.sync.aligned.m64n64k16.f32.bf16.bf16 "
      "{%0, %1, %2, %3, %4, %5, %6, %7, %8, %9, %10, %11, %12, %13, %14, %15, %16, %17, %18, %19, %20, %21, %22, %23, %24, %25, %26, %27, %28, %29, %30, %31}, "
      "da, db, p, 1, 1, 0, 1;\n}\n"
      :
      "+f"(d[0]), "+f"(d[1]), "+f"(d[2]), "+f"(d[3]), "+f"(d[4]), "+f"(d[5]), "+f"(d[6]), "+f"(d[7]),
      "+f"(d[8]), "+f"(d[9]), "+f"(d[10]), "+f"(d[11]), "+f"(d[12]), "+f"(d[13]), "+f"(d[14]), "+f"(d[15]),
      "+f"(d[16]), "+f"(d[17]), "+f"(d[18]), "+f"(d[19]), "+f"(d[20]), "+f"(d[21]), "+f"(d[22]), "+f"(d[23]),
      "+f"(d[24]), "+f"(d[25]), "+f"(d[26]), "+f"(d[27]), "+f"(d[28]), "+f"(d[29]), "+f"(d[30]), "+f"(d[31])
      : "r"(da), "r"(db), "r"(scale_d), "n"(AHI));
}
__device__ __forceinline__ void wgmma_n64_f16t(float (&d)[32], uint32_t da, uint32_t db, int scale_d) {
  asm volatile(
      "{\n.reg .pred p;\n.reg .b64 da, db;\nsetp.ne.b32 p, %34, 0;\n"
      "mov.b64 da, {%32, 0x40000040};\nmov.b64 db, {%33, 0x40000040};\n"
      "wgmma.mma_async.sync.aligned.m64n64k16.f32.f16.f16 "
      "{%0, %1, %2, %3, %4, %5, %6, %7, %8, %9, %10, %11, %12, %13, %14, %15, %16, %17, %18, %19, %20, %21, %22, %23, %24, %25, %26, %27, %28, %29, %30, %31}, "
      "da, db, p, 1, 1, 1, 1;\n}\n"
      :
      "+f"(d[0]), "+f"(d[1]), "+f"(d[2]), "+f"(d[3]), "+f"(d[4]), "+f"(d[5]), "+f"(d[6]), "+f"(d[7]),
      "+f"(d[8]), "+f"(d[9]), "+f"(d[10]), "+f"(d[11]), "+f"(d[12]), "+f"(d[13]), "+f"(d[14]), "+f"(d[15]),
      "+f"(d[16]), "+f"(d[17]), "+f"(d[18]), "+f"(d[19]), "+f"(d[20]), "+f"(d[21]), "+f"(d[22]), "+f"(d[23]),
      "+f"(d[24]), "+f"(d[25]), "+f"(d[26]), "+f"(d[27]), "+f"(d[28]), "+f"(d[29]), "+f"(d[30]), "+f"(d[31])
      : "r"(da), "r"(db), "r"(scale_d));
}
__device__ __forceinline__ uint32_t pack_bf16(float lo, float hi) {
  uint32_t r;
  asm("cvt.rn.bf16x2.f32 %0, %1, %2;" : "=r"(r) : "f"(hi), "f"(lo));
  return r;
}
__device__ __forceinline__ uint32_t pack_bf16_relu(float lo, float hi) {
  uint32_t r;
  asm("cvt.rn.relu.bf16x2.f32 %0, %1, %2;" : "=r"(r) : "f"(hi), "f"(lo));
  return r;
}
__device__ __forceinline__ uint32_t mul_bf16x2(uint32_t a, uint32_t b) {
  uint32_t r;
  asm("mul.rn.bf16x2 %0, %1, %2;" : "=r"(r) : "r"(a), "r"(b));
  return r;
}
__device__ __forceinline__ void stmatrix_x4(uint32_t addr, uint32_t r0, uint32_t r1, uint32_t r2, uint32_t r3) {
  asm volatile("stmatrix.sync.aligned.m8n8.x4.shared.b16 [%0], {%1, %2, %3, %4};"
               ::"r"(addr), "r"(r0), "r"(r1), "r"(r2), "r"(r3) : "memory");
}
__device__ __forceinline__ void sts128(uint32_t addr, uint32_t a, uint32_t b, uint32_t c, uint32_t d) {
  asm volatile("st.shared.v4.b32 [%0], {%1, %2, %3, %4};" ::"r"(addr), "r"(a), "r"(b), "r"(c), "r"(d) : "memory");
}
__device__ __forceinline__ uint4 lds128(uint32_t addr) {
  uint4 v;
  asm volatile("ld.shared.v4.b32 {%0, %1, %2, %3}, [%4];" : "=r"(v.x), "=r"(v.y), "=r"(v.z), "=r"(v.w) : "r"(addr) : "memory");
  return v;
}
__device__ __forceinline__ float bf_lo(uint32_t v) { return __uint_as_float(v << 16); }
__device__ __forceinline__ float bf_hi(uint32_t v) { return __uint_as_float(v & 0xFFFF0000u); }

struct C2 { __half2 x, y; };
__device__ __forceinline__ C2 cadd(C2 a, C2 b) { return {__hadd2(a.x, b.x), __hadd2(a.y, b.y)}; }
__device__ __forceinline__ C2 csub(C2 a, C2 b) { return {__hsub2(a.x, b.x), __hsub2(a.y, b.y)}; }
template <int SG> __device__ __forceinline__ C2 cmul(C2 a, __half2 c, __half2 s) {
  return SG > 0 ? C2{__hfma2(a.x, c, __hneg2(__hmul2(a.y, s))), __hfma2(a.x, s, __hmul2(a.y, c))}
                : C2{__hfma2(a.x, c, __hmul2(a.y, s)), __hfma2(a.y, c, __hneg2(__hmul2(a.x, s)))};
}
template <int SG> __device__ __forceinline__ C2 ctw(C2 a, __half2 w) { return cmul<SG>(a, __low2half2(w), __high2half2(w)); }
template <int SG> __device__ __forceinline__ C2 mul_i(C2 a) {
  return SG > 0 ? C2{__hneg2(a.y), a.x} : C2{a.y, __hneg2(a.x)};
}
template <int SG> __device__ __forceinline__ void fft4(C2& a0, C2& a1, C2& a2, C2& a3) {
  C2 t0 = cadd(a0, a2), t1 = csub(a0, a2), t2 = cadd(a1, a3), d = csub(a1, a3);
  a0 = cadd(t0, t2); a2 = csub(t0, t2);
  if (SG > 0) { a1 = {__hsub2(t1.x, d.y), __hadd2(t1.y, d.x)}; a3 = {__hadd2(t1.x, d.y), __hsub2(t1.y, d.x)}; }
  else        { a1 = {__hadd2(t1.x, d.y), __hsub2(t1.y, d.x)}; a3 = {__hsub2(t1.x, d.y), __hadd2(t1.y, d.x)}; }
}
template <int SG> __device__ __forceinline__ void bfly_tw(C2 a, C2 b, __half2 c, __half2 s, C2& p, C2& m) {
  const __half2 two = __float2half2_rn(2.0f);
  if (SG > 0) p = C2{__hfma2(__hneg2(b.y), s, __hfma2(b.x, c, a.x)), __hfma2(b.x, s, __hfma2(b.y, c, a.y))};
  else        p = C2{__hfma2(b.y, s, __hfma2(b.x, c, a.x)), __hfma2(__hneg2(b.x), s, __hfma2(b.y, c, a.y))};
  m = C2{__hfma2(a.x, two, __hneg2(p.x)), __hfma2(a.y, two, __hneg2(p.y))};
}
template <int SG> __device__ __forceinline__ void fft4_tail(C2 t0, C2 t1, C2 t2, C2 d, C2& a0, C2& a1, C2& a2, C2& a3) {
  a0 = cadd(t0, t2); a2 = csub(t0, t2);
  if (SG > 0) { a1 = {__hsub2(t1.x, d.y), __hadd2(t1.y, d.x)}; a3 = {__hadd2(t1.x, d.y), __hsub2(t1.y, d.x)}; }
  else        { a1 = {__hadd2(t1.x, d.y), __hsub2(t1.y, d.x)}; a3 = {__hsub2(t1.x, d.y), __hadd2(t1.y, d.x)}; }
}
template <int SG> __device__ __forceinline__ void fft4_tw(C2& a0, C2& a1, C2& a2, C2& a3, __half2 c2, __half2 s2, __half2 c3, __half2 s3) {
  C2 t0, t1, t2, d;
  bfly_tw<SG>(a0, a2, c2, s2, t0, t1);
  bfly_tw<SG>(a1, a3, c3, s3, t2, d);
  fft4_tail<SG>(t0, t1, t2, d, a0, a1, a2, a3);
}
template <int SG> __device__ __forceinline__ void fft16_second(C2 (&v)[16]) {
  const __half2 C1 = __float2half2_rn(0.92387953251128674f), S1 = __float2half2_rn(0.38268343236508977f);
  const __half2 R = __float2half2_rn(0.70710678118654752f), NR = __float2half2_rn(-0.70710678118654752f);
  const __half2 NC1 = __float2half2_rn(-0.92387953251128674f), NS1 = __float2half2_rn(-0.38268343236508977f);
  fft4<SG>(v[0], v[1], v[2], v[3]);
  v[5] = cmul<SG>(v[5], C1, S1);
  fft4_tw<SG>(v[4], v[5], v[6], v[7], R, R, S1, C1);
  {
    v[9] = cmul<SG>(v[9], R, R);
    const C2 r = mul_i<SG>(v[10]);
    C2 t2, d;
    bfly_tw<SG>(v[9], v[11], NR, R, t2, d);
    fft4_tail<SG>(cadd(v[8], r), csub(v[8], r), t2, d, v[8], v[9], v[10], v[11]);
  }
  v[13] = cmul<SG>(v[13], S1, C1);
  fft4_tw<SG>(v[12], v[13], v[14], v[15], NR, R, NC1, NS1);
  C2 t;
  t = v[1]; v[1] = v[4]; v[4] = t;   t = v[2]; v[2] = v[8]; v[8] = t;   t = v[3]; v[3] = v[12]; v[12] = t;
  t = v[6]; v[6] = v[9]; v[9] = t;   t = v[7]; v[7] = v[13]; v[13] = t; t = v[11]; v[11] = v[14]; v[14] = t;
}
template <int SG> __device__ __forceinline__ void fft16(C2 (&v)[16]) {
#pragma unroll
  for (int b = 0; b < 4; b++) fft4<SG>(v[b], v[4 + b], v[8 + b], v[12 + b]);
  fft16_second<SG>(v);
}
template <int SG> __device__ __forceinline__ void fft16_pre(C2 (&v)[16], const __half2 (&w)[16]) {
#pragma unroll
  for (int b = 0; b < 4; b++) {
    if (b) v[b] = ctw<SG>(v[b], w[b]);
    v[4 + b] = ctw<SG>(v[4 + b], w[4 + b]);
    fft4_tw<SG>(v[b], v[4 + b], v[8 + b], v[12 + b], __low2half2(w[8 + b]), __high2half2(w[8 + b]),
                __low2half2(w[12 + b]), __high2half2(w[12 + b]));
  }
  fft16_second<SG>(v);
}
template <int SG> __device__ __forceinline__ void fft8_second(C2 (&e)[4], C2 (&o)[4], C2* v) {
  const __half2 R = __float2half2_rn(0.70710678118654752f), NR = __float2half2_rn(-0.70710678118654752f);
  fft4<SG>(e[0], e[1], e[2], e[3]);
  o[1] = cmul<SG>(o[1], R, R);
  const C2 r = mul_i<SG>(o[2]);
  C2 t2, d;
  bfly_tw<SG>(o[1], o[3], NR, R, t2, d);
  fft4_tail<SG>(cadd(o[0], r), csub(o[0], r), t2, d, o[0], o[1], o[2], o[3]);
#pragma unroll
  for (int k = 0; k < 4; k++) { v[2 * k] = e[k]; v[2 * k + 1] = o[k]; }
}
template <int SG> __device__ __forceinline__ void fft8(C2* v) {
  C2 e[4], o[4];
#pragma unroll
  for (int b = 0; b < 4; b++) { e[b] = cadd(v[b], v[4 + b]); o[b] = csub(v[b], v[4 + b]); }
  fft8_second<SG>(e, o, v);
}
__device__ __forceinline__ uint32_t h2u(__half2 h) { return *reinterpret_cast<uint32_t*>(&h); }
__device__ __forceinline__ __half2 u2h(uint32_t u) { return *reinterpret_cast<__half2*>(&u); }
__device__ __forceinline__ void sts_c2(uint32_t addr, C2 v) {
  asm volatile("st.shared.v2.b32 [%0], {%1, %2};" ::"r"(addr), "r"(h2u(v.x)), "r"(h2u(v.y)) : "memory");
}
__device__ __forceinline__ C2 lds_c2(uint32_t addr) {
  uint32_t a, b;
  asm volatile("ld.shared.v2.b32 {%0, %1}, [%2];" : "=r"(a), "=r"(b) : "r"(addr) : "memory");
  return C2{u2h(a), u2h(b)};
}
__device__ __forceinline__ uint32_t bf2_to_h2(uint32_t w, uint32_t nbias) {
  return (__viaddmax_s16x2(w & 0x7FFF7FFFu, nbias, 0u) << 3) | (w & 0x80008000u);
}
template <int N> __device__ __forceinline__ uint32_t acc_max_exp(uint32_t m, const uint32_t (&w)[N]) {
#pragma unroll
  for (int i = 0; i < N; i += 2) m = __vimax3_s16x2(m, w[i] & 0x7F807F80u, w[i + 1] & 0x7F807F80u);
  return m;
}
__device__ __forceinline__ uint32_t warp_max_exp(uint32_t m) { return __reduce_max_sync(0xffffffffu, max(m >> 23, (m & 0xFFFFu) >> 7)); }

__device__ __forceinline__ uint32_t g2_buf(int b) {
  return ((0x532410u >> (4 * b)) & 7u) * 32768u;
}

__device__ __forceinline__ uint32_t z_buf(int z) { return g2_buf(z < 2 ? 2 : 3) + (z & 1) * 16384; }
__device__ __forceinline__ uint32_t g2_seq(int i) { return (uint32_t)(0x10dcba98543210ull >> (4 * i)) & 15u; }
__device__ __forceinline__ int g1_chunk(int j, int tile) { return 7 * (j >> 1) + (tile == 3 ? 6 : 3 * (j & 1) + tile); }
__device__ __forceinline__ int g2_chunk(int kh, int i) {
  return i < 12 ? 7 * (i & 3) + 3 * kh + (i >> 2) : 7 * (2 * kh + i - 12) + 6;
}

__device__ __forceinline__ void epi_h(const float (&a)[64], uint32_t st_addr, int lane) {
#pragma unroll
  for (int jb = 0; jb < 8; jb += 2) {
    uint32_t r[4];
#pragma unroll
    for (int q = 0; q < 4; q++) {
      int i = 4 * jb + 2 * q;
      r[q] = mul_bf16x2(pack_bf16_relu(a[i], a[i + 1]), pack_bf16(a[32 + i], a[32 + i + 1]));
    }
    uint32_t grp = jb + (lane >> 4);
    stmatrix_x4(st_addr + ((grp ^ (lane & 7)) << 4), r[0], r[1], r[2], r[3]);
  }
}

__global__ void __cluster_dims__(2, 1, 1) __launch_bounds__(512, 1)
fused_kernel(const __grid_constant__ CUtensorMap map_x, const __grid_constant__ CUtensorMap map_wg,
             const __grid_constant__ CUtensorMap map_wu, const __grid_constant__ CUtensorMap map_wd,
             const __grid_constant__ CUtensorMap map_y, const __grid_constant__ CUtensorMap map_z,
             const __grid_constant__ CUtensorMap map_w, const __grid_constant__ CUtensorMap map_gn,
             const __grid_constant__ CUtensorMap map_un, const __grid_constant__ CUtensorMap map_o,
             const __nv_bfloat16* __restrict__ x_ptr, const __nv_bfloat16* __restrict__ w_r, const __nv_bfloat16* __restrict__ w_i,
             const __nv_bfloat16* __restrict__ wd_ptr, const __nv_bfloat16* __restrict__ gate_w,
             __nv_bfloat16* __restrict__ out) {
  extern __shared__ __align__(1024) uint8_t smem[];
  const uint32_t sb = smem_u32(smem);
  const uint32_t bar0 = sb + OFF_BAR;
  const int tid = threadIdx.x, lane = tid & 31;
  const int warp = __shfl_sync(0xffffffffu, tid >> 5, 0);
  const int cl = blockIdx.x >> 1, kh = blockIdx.x & 1;
  int grp, p;
  if (cl < 4) { grp = 15; p = cl; }
  else if (cl < 36) { grp = (cl - 4) & 7; p = (cl - 4) >> 3; }
  else { grp = 8 + (cl - 36) % 7; p = (cl - 36) / 7; }
  const int kq = grp & 1, r = (grp & 14) + kh, j = 4 * kq + p;
  const bool extra = blockIdx.x >= 128;
#define BAR(i) (bar0 + 8u * (i))

  if (!extra) {
    if (warp == 15 && lane == 0) bulk_prefetch(x_ptr + (size_t)(r * 128 + 16 * j) * 512, 16384);
    if (warp == 12) {
      if (lane == 0) {
#pragma unroll
        for (int kk = 0; kk < 8; kk++) mbar_init(BAR(B_XFULL + kk), 1);
        asm volatile("fence.mbarrier_init.release.cluster;" ::: "memory");
      }
      __syncwarp();
#pragma unroll
      for (int kk = 0; kk < 8; kk++) {
        mbar_expect_tx_e(BAR(B_XFULL + kk), 16384);
        tma2d_e(sb + OFF_X + kk * 16384, &map_x, kk * 64, r * 128, BAR(B_XFULL + kk));
      }
      bar_arrive(4, 288);
    }
    if (warp < 8) {
      const int cc = 64 * (j >> 1) + 2 * lane + (j & 1), u0 = warp * 4;
      const float c2 = 2.0f * __cosf((float)cc * (3.14159265358979f / 256.0f));
      const uint32_t r7 = lane & 6;
      const uint32_t rowaddr = sb + OFF_ST + (u0 >> 3) * 8192 + (uint32_t)(16 * (lane >> 3) + 8 * (lane & 1) + r7) * 128u;
#pragma unroll 1
      for (int u = u0; u < u0 + 4; u++) {
        uint32_t pc[4], ps[4];
        const int ph = cc * 8 * u;
        const float an0 = (float)(ph & 511) * (-3.14159265358979f / 256.0f), an1 = (float)((ph + cc) & 511) * (-3.14159265358979f / 256.0f);
        float ca = __cosf(an0), cb = __cosf(an1), sa = __sinf(an0), sc = __sinf(an1);
#pragma unroll
        for (int e = 0; e < 4; e++) {
          pc[e] = pack_bf16(ca, cb);
          ps[e] = (cc == 0) ? 0xBF803F80u : pack_bf16(sa, sc);
          if (e < 3) {
            ca = c2 * cb - ca; cb = c2 * ca - cb;
            sa = c2 * sc - sa; sc = c2 * sa - sc;
          }
        }
        const uint32_t ch = (uint32_t)(u & 7) ^ r7;
        sts128(rowaddr + (ch << 4), pc[0], pc[1], pc[2], pc[3]);
        sts128(rowaddr + 128 + ((ch ^ 1) << 4), ps[0], ps[1], ps[2], ps[3]);
      }
      fence_async_smem();
      if (warp >= 4) bar_arrive(4, 288);
    }
    if (warp == 13 && lane == 0) {
#pragma unroll
      for (int i = B_RFULL; i < (int)B_COUNT; i++) {
        uint32_t cnt = 1;
        if (i >= (int)B_REMPTY && i < (int)B_G2FULL) cnt = 2;
        if (i >= (int)B_G2EMPTY && i < (int)B_STFULL) cnt = 4;
        if (i >= (int)B_STFULL && i < (int)B_STEMPTY) cnt = 128;
        if (i == (int)B_GFULL) cnt = 32;
        if (i == (int)B_WFULL) cnt = 128;
        if (i == (int)B_GDONE || i == (int)B_YMAX) cnt = 4;
        if (i >= (int)B_ZFULL && i < (int)B_FFDONE) cnt = 2;
        mbar_init(BAR(i), cnt);
      }
      asm volatile("st.shared.b32 [%0], %1;" ::"r"(sb + OFF_READY), "r"(0) : "memory");
      asm volatile("fence.mbarrier_init.release.cluster;" ::: "memory");
    }
    if (warp == 14 && lane == 0) {
      tma2d_prefetch(kh ? &map_wu : &map_wg, g1_chunk(j, 0) * 64, (r >> 1) * 64);
      bulk_prefetch(gate_w, 1024);
    }
    __syncwarp();
    cluster_arrive();
    if (warp < 4) {
      const int w4 = warp;
      const bool lead = tid == 0;
      float acc0[64];
      bar_sync(4, 288);
#pragma unroll 1
      for (int kk = 0; kk < ((j & 1) ? 4 : 8); kk++) {
        mbar_wait_u(BAR(B_XFULL + kk), 0);
        const uint32_t da = desc_k(sb + OFF_ST + (kk & 3) * 8192), db = desc_k(sb + OFF_X + kk * 16384);
        wgmma_fence();
#pragma unroll
        for (int k = 0; k < 4; k++) wgmma_n128<0, 0>(acc0, da + 2 * k, db + 2 * k, (kk | k) != 0);
        wgmma_commit();
      }
      if (j & 1) {
#pragma unroll 1
        for (int kk = 0; kk < 4; kk++) {
          mbar_wait_u(BAR(B_XFULL + 4 + kk), 0);
          const uint32_t da = desc_k(sb + OFF_ST + kk * 8192), db = desc_k(sb + OFF_X + 65536 + kk * 16384);
          wgmma_fence();
#pragma unroll
          for (int k = 0; k < 4; k++) wgmma_n128<0, 0, -1>(acc0, da + 2 * k, db + 2 * k, 1);
          wgmma_commit();
        }
      }
      bar_arrive(8, 256);
      cluster_wait();
      wgmma_wait<0>();
      bar_sync(5, 128);
      mbar_arrive_if(BAR(B_TABFREE), lead);
      const uint32_t yrow = sb + OFF_FF + (uint32_t)(8 * w4 + (lane >> 2)) * 128u;
#pragma unroll
      for (int g = 0; g < 4; g++) {
#pragma unroll
        for (int e = 0; e < 2; e++) {
          const uint32_t ch = (uint32_t)(2 * (lane & 3) + e) ^ (uint32_t)(lane >> 2);
          const int i0 = 16 * g + e;
          sts128(yrow + g * 4096 + (ch << 4), pack_bf16(acc0[i0], acc0[i0 + 2]), pack_bf16(acc0[i0 + 4], acc0[i0 + 6]),
                 pack_bf16(acc0[i0 + 8], acc0[i0 + 10]), pack_bf16(acc0[i0 + 12], acc0[i0 + 14]));
        }
      }
      fence_async_smem();
      mbar_arrive(BAR(B_STFULL + 0));
      {
        float m = 0.f;
#pragma unroll
        for (int i = 0; i < 64; i++) m = fmaxf(m, fabsf(acc0[i]));
        const uint32_t me = __reduce_max_sync(0xffffffffu, pack_bf16(m, 0.f) >> 7);
        asm volatile(ELECT "st.shared.b32 [%0], %1;\n}" ::"r"(sb + OFF_TW2 + 480 + w4 * 4), "r"(me) : "memory");
        asm volatile(ELECT "mbarrier.arrive.shared::cta.b64 _, [%0];\n}" ::"r"(BAR(B_YMAX)) : "memory");
      }
    }
  }

  if (warp < 8) {
    asm volatile("setmaxnreg.inc.sync.aligned.u32 168;");
    if (extra) return;
    const int wg = warp >> 2, w4 = warp & 3, t128 = tid & 127;
    const uint32_t rempty_peer = mapa(BAR(B_REMPTY), kh ^ 1);
    const bool lead = t128 == 0;
#define RELEASE_SLOT(sl, pr) do { mbar_arrive_if(BAR(B_REMPTY + (sl)), pr); mbar_arrive_remote_if(rempty_peer + 8u * (sl), pr); } while (0)
#define RELEASE_BUF(b, pr) RELEASE_SLOT(B_G2EMPTY - B_REMPTY + (b), pr)
    float acc0[64], acc1[64];
    const uint32_t st_lane = sb + OFF_ST + (uint32_t)(16 * w4 + (lane & 7) + ((lane >> 3) & 1) * 8) * 128u;
    if (wg == 1) cluster_wait();
#pragma unroll 1
    for (int t = wg ^ 1; t < 3; t += 2) {
      if (wg) bar_sync(8, 256); else bar_sync(9, 256);
#pragma unroll 1
      for (int kk = 0; kk < 8; kk++) {
        const uint32_t slot = kk & 3, par = (uint32_t)(kk >> 2);
        mbar_wait_u(BAR(B_RFULL + wg * 4 + slot), par);
        const uint32_t da = desc_k(sb + OFF_X + kk * 16384), db = desc_mn(sb + OFF_R + slot * 16384);
        wgmma_fence();
#pragma unroll
        for (int k = 0; k < 4; k++) {
          wgmma_n128<0, 1>(acc0, da + 2 * k, db + 128 * k, (kk | k) != 0);
          wgmma_n128<0, 1>(acc1, da + 512 + 2 * k, db + 128 * k, (kk | k) != 0);
        }
        wgmma_commit();
        wgmma_wait<1>();
        RELEASE_SLOT((kk - 1) & 3, lead && kk > 0);
        RELEASE_BUF((kk >> 1) - 1, lead && t == 2 && kk >= 2 && !(kk & 1));
        RELEASE_BUF(3, lead && t == 2 && kk == 6);
      }
      if (t == 0) bar_arrive(9, 256);
      if (t == 1) bar_arrive(8, 256);
      wgmma_wait<0>();
      RELEASE_SLOT(3, lead);
      RELEASE_BUF(4, lead && t == 2);
      RELEASE_BUF(5, lead && t == 2);
      mbar_wait_u(BAR(B_STEMPTY + 1 + t), 0);
      epi_h(acc0, st_lane, lane);
      epi_h(acc1, st_lane + 8192, lane);
      fence_async_smem();
      mbar_arrive(BAR(B_STFULL + 1 + t));
    }
    if (wg == 0) {
      mbar_wait_u(BAR(B_GDONE), 0);
#define N_RELEASE(st, pr) do { RELEASE_BUF((st) + ((st) >= 2), pr); RELEASE_BUF(2, (pr) && (st) == 1); } while (0)
#pragma unroll 1
      for (int st = 0; st < 4; st++) {
        mbar_wait_u(BAR(B_RFULL + st), 0);
        const uint32_t da = desc_mn(sb + OFF_R + st * 16384), db = desc_k(sb + OFF_X + st * 32768);
        wgmma_fence();
#pragma unroll
        for (int k = 0; k < 8; k++) wgmma_n128<1, 0>(acc1, da + 64 * k, db + (k >> 2) * 1024 + 2 * (k & 3), (st | k) != 0, HI64);
        wgmma_commit();
        wgmma_wait<1>();
        N_RELEASE(st - 1, lead && st > 2);
        if (st < 2) {
          wgmma_wait<0>();
          N_RELEASE(st, lead);
        }
      }
      bar_arrive(10, 256);
      wgmma_wait<0>();
      RELEASE_BUF(4, lead);
      uint32_t keep[16];
      const uint32_t xs = sb + OFF_NST + 8192 + lane * 16;
      if (w4 < 2) {
#pragma unroll
        for (int i = 0; i < 4; i++)
          sts128(xs + w4 * 2048 + i * 512, pack_bf16_relu(acc1[32 + 8 * i], acc1[33 + 8 * i]), pack_bf16_relu(acc1[34 + 8 * i], acc1[35 + 8 * i]),
                 pack_bf16_relu(acc1[36 + 8 * i], acc1[37 + 8 * i]), pack_bf16_relu(acc1[38 + 8 * i], acc1[39 + 8 * i]));
#pragma unroll
        for (int i = 0; i < 16; i++) keep[i] = pack_bf16_relu(acc1[2 * i], acc1[2 * i + 1]);
      } else {
#pragma unroll
        for (int i = 0; i < 4; i++)
          sts128(xs + w4 * 2048 + i * 512, pack_bf16(acc1[8 * i], acc1[1 + 8 * i]), pack_bf16(acc1[2 + 8 * i], acc1[3 + 8 * i]),
                 pack_bf16(acc1[4 + 8 * i], acc1[5 + 8 * i]), pack_bf16(acc1[6 + 8 * i], acc1[7 + 8 * i]));
#pragma unroll
        for (int i = 0; i < 16; i++) keep[i] = pack_bf16(acc1[32 + 2 * i], acc1[33 + 2 * i]);
      }
      bar_sync(7, 128);
      const uint32_t hl = sb + OFF_NST + (uint32_t)(64 * (w4 >> 1) + 8 * (lane >> 4) + (lane & 7)) * 64u
                        + (((uint32_t)(2 * (w4 & 1) + ((lane >> 3) & 1)) ^ (uint32_t)((lane >> 1) & 3)) << 4);
#pragma unroll
      for (int i = 0; i < 4; i++) {
        const uint4 o = lds128(xs + (w4 ^ 2) * 2048 + i * 512);
        asm volatile("stmatrix.sync.aligned.m8n8.x4.trans.shared.b16 [%0], {%1, %2, %3, %4};"
                     ::"r"(hl + i * 1024), "r"(mul_bf16x2(keep[4 * i], o.x)), "r"(mul_bf16x2(keep[4 * i + 1], o.y)),
                       "r"(mul_bf16x2(keep[4 * i + 2], o.z)), "r"(mul_bf16x2(keep[4 * i + 3], o.w)) : "memory");
      }
      bar_arrive(1, 256);
      fence_async_smem();
      mbar_arrive(BAR(B_STFULL + 4));
    } else {
      bar_sync(10, 256);
    }
    {
      uint32_t prev = 1;
#pragma unroll 1
      for (int i = 0; i < 10; i++) {
        const uint32_t bp = g2_seq(i), b = bp & 7u;
        if (wg == 1 && i == 1) bar_sync(1, 256);
        if (i == 0) mbar_wait_u(BAR(B_FFTOUT), 0);
        mbar_wait_u(BAR(B_G2FULL + b), bp >> 3);
        const uint32_t buf = sb + g2_buf(b);
        const uint32_t da = desc_k(buf + wg * 8192), db = desc_mn(buf + 16384);
        wgmma_fence();
#pragma unroll
        for (int k = 0; k < 4; k++) wgmma_n128<0, 1>(acc0, da + 2 * k, db + 128 * k, (i | k) != 0);
        wgmma_commit();
        wgmma_wait<1>();
        RELEASE_BUF(prev, lead && i != 0);
        prev = b;
      }
    }
    {
      float az[32], cs[32], ck[32];
#define HALF_STAGE(acc, i, boff, first) do {                                                                   \
        const uint32_t da = desc_k(sb + g2_buf(i) + wg * 8192), db = desc_mn(sb + g2_buf(i) + (boff));         \
        _Pragma("unroll") for (int k = 0; k < 4; k++) wgmma_n64_bf<HI128>(acc, da + 2 * k, db + 128 * k, !(first) || k != 0); \
      } while (0)
#define HALF_STAGE_N(acc, i, boff, first) do {                          \
        const uint32_t da = desc_k(sb + g2_buf(i) + wg * 4096), db = desc_mn(sb + g2_buf(i) + (boff));         \
        _Pragma("unroll") for (int k = 0; k < 4; k++)                                                          \
          wgmma_n64_bf<HI64>(acc, da + 2 * (k & 1) + (k >> 1) * 512, db + 128 * k, !(first) || k != 0);        \
      } while (0)
#define Z_STAGE(z) do {                                                                                        \
        mbar_wait_u(BAR(B_ZFULL + (z)), 0);                                                                    \
        const uint32_t da = desc_mn(sb + z_buf(z) + wg * 8192), db = desc_mn(sb + OFF_ST + (z) * 8192);        \
        wgmma_fence();                                                                                         \
        _Pragma("unroll") for (int k = 0; k < 4; k++) wgmma_n64_f16t(az, da + 128 * k, db + 128 * k, (z) != 0 || k != 0); \
      } while (0)
      mbar_wait_u(BAR(B_G2FULL + 4), 1);
      wgmma_fence();
      HALF_STAGE(cs, 4, 24576, true);
      wgmma_commit();
      wgmma_wait<1>();
      RELEASE_BUF(3, lead);
      mbar_wait_u(BAR(B_G2FULL + 5), 1);
      wgmma_fence();
      HALF_STAGE(cs, 5, 24576, false);
      mbar_wait_u(BAR(B_G2FULL + 0), 0);
      wgmma_fence();
      HALF_STAGE_N(cs, 0, 24576, false);
      mbar_wait_u(BAR(B_G2FULL + 1), 0);
      wgmma_fence();
      HALF_STAGE_N(cs, 1, 24576, false);
      wgmma_commit();
      mbar_wait_u(BAR(B_GFULL), 0);
      const float* gs = reinterpret_cast<const float*>(smem + OFF_G);
      float g0 = gs[64 * wg + 16 * w4 + (lane >> 2)], g1 = gs[64 * wg + 16 * w4 + (lane >> 2) + 8];
      const uint32_t gbp = pack_bf16(1.0f - g0, 1.0f - g1);
      const float gb0 = bf_lo(gbp), gb1 = bf_hi(gbp);
      {
        const uint32_t ex = ld_volatile_shared(sb + OFF_EXP);
        const int ew = max((int)(ex & 0xFFu) - 22, 0), eref = max((int)((ex >> 8) & 0xFFu) - 12, 6);
        const float s1 = __uint_as_float((uint32_t)(ew + 14) << 23), s2 = __uint_as_float((uint32_t)min(eref + 5, 254) << 23);
        g0 = g0 * s1 * s2; g1 = g1 * s1 * s2;
      }
      const float gu0 = kq ? -g0 : g0, gu1 = kq ? -g1 : g1;
      const uint32_t stg = sb + z_buf(0) + wg * 8192 + w4 * 2048;
      const uint32_t srow = stg + (uint32_t)(lane & 15) * 128u;
      const int orow = r * 128 + 64 * wg + 16 * w4;
      Z_STAGE(0);
      wgmma_commit();
      wgmma_wait<1>();
#pragma unroll
      for (int i = 0; i < 32; i++) acc0[32 + i] = ((i & 2) ? gb1 : gb0) * (acc0[32 + i] + cs[i]);
      Z_STAGE(1);
      Z_STAGE(2);
      Z_STAGE(3);
      wgmma_commit();
      HALF_STAGE_N(ck, 1, 16384, true);
      wgmma_commit();
      wgmma_wait<1>();
#pragma unroll
      for (int jb = 0; jb < 8; jb += 2) {
        uint32_t pk[4];
#pragma unroll
        for (int c = 0; c < 4; c++) {
          const int x = 4 * jb + 2 * c;
          const float g = (c & 1) ? g1 : g0;
          pk[c] = pack_bf16(g * az[x] + acc0[32 + x], g * az[x + 1] + acc0[33 + x]);
        }
        stmatrix_x4(srow + (((jb + (lane >> 4)) ^ (lane & 7)) << 4), pk[0], pk[1], pk[2], pk[3]);
      }
      fence_async_smem();
      __syncwarp();
      asm volatile(ELECT "cp.reduce.async.bulk.tensor.2d.global.shared::cta.add.bulk_group [%0, {%1, %2}], [%3];\n}"
                   ::"l"(&map_o), "r"(p * 64 + (kq ^ 1) * 256), "r"(orow), "r"(stg) : "memory");
      wgmma_fence();
      HALF_STAGE_N(ck, 0, 16384, false);
      HALF_STAGE(ck, 4, 16384, false);
      HALF_STAGE(ck, 5, 16384, false);
      wgmma_commit();
#pragma unroll
      for (int i = 0; i < 32; i++) acc0[i] = ((i & 2) ? gb1 : gb0) * acc0[i] + ((i & 2) ? gu1 : gu0) * az[i];
      wgmma_wait<0>();
      const uint32_t d23 = 16384;
#pragma unroll
      for (int jb = 0; jb < 8; jb += 2) {
        uint32_t pk[4];
#pragma unroll
        for (int c = 0; c < 4; c++) {
          const int x = 4 * jb + 2 * c;
          const float gb = (c & 1) ? gb1 : gb0;
          pk[c] = pack_bf16(gb * ck[x] + acc0[x], gb * ck[x + 1] + acc0[x + 1]);
        }
        stmatrix_x4(srow + d23 + (((jb + (lane >> 4)) ^ (lane & 7)) << 4), pk[0], pk[1], pk[2], pk[3]);
      }
      fence_async_smem();
      __syncwarp();
      asm volatile(ELECT "cp.reduce.async.bulk.tensor.2d.global.shared::cta.add.bulk_group [%0, {%1, %2}], [%3];\n}"
                   ::"l"(&map_o), "r"(p * 64 + kq * 256), "r"(orow), "r"(stg + d23) : "memory");
      bulk_commit();
      bulk_wait_read();
    }
  } else if (warp < 12) {
    if (extra && kh) return;
    const int t128 = tid & 127, w4 = warp & 3;
    const unsigned e = __ldcg(&g_Sync[blockIdx.x * 32]) + 1;
    const int P = extra ? 0 : blockIdx.x;
    const int k1 = t128 >> 3, q = t128 & 7;
    const int t = 32 * w4 + 8 * (lane & 3) + (lane >> 2);
    const int u = t128 & 63, qh = t128 >> 6;
    const int krow = (P >> 3) + 128 * ((P >> 2) & 1) + 512 * (P & 3);
    uint2 ra[16], rb[16];
    {
      const int eo = (((krow + 64 * qh) * 257) >> 2) + u;
      const uint2* srcr = reinterpret_cast<const uint2*>(w_r) + eo;
      const uint2* srci = reinterpret_cast<const uint2*>(w_i) + eo;
#pragma unroll
      for (int i = 0; i < 16; i++) {
        const uint2* src = ((i & 2) ? srci : srcr) + ((i >> 2) * 4 + (i & 1) * 64) * 257;
        ra[i] = __ldg(src);
        rb[i] = make_uint2(0u, 0u);
        if (lane == 31) rb[i] = __ldg(src + 1);
      }
    }
    if (!extra) {
      {
        const int ab = w4 & 1, cp = w4 >> 1;
        const int cc = 64 * (P >> 5) + 4 * (P & 15) + 2 * ab + ((P >> 4) & 1);
        const int fr = (cc == 0 && cp) ? 256 : cc, ph0 = (cp && cc) ? 128 : 0;
        const float amp = cc == 0 ? 0.5f : 1.0f;
        uint32_t pk[4];
#pragma unroll
        for (int i = 0; i < 4; i++) {
          const int d = 8 * lane + 2 * i;
          pk[i] = h2u(__floats2half2_rn(amp * __cosf((float)(((fr * d + ph0 + 256) & 511) - 256) * (3.14159265358979f / 256.0f)),
                                        amp * __cosf((float)(((fr * (d + 1) + ph0 + 256) & 511) - 256) * (3.14159265358979f / 256.0f))));
        }
        const int rl = 16 * ((P & 15) >> 2) + 2 * (P & 3) + cp + 8 * ab;
        __stcg(reinterpret_cast<uint4*>(g_T + (size_t)((P >> 4) * 4 + (lane >> 3)) * 8192 + rl * 128 + (((lane & 7) ^ (rl & 7)) << 4)),
               make_uint4(pk[0], pk[1], pk[2], pk[3]));
      }
      cluster_wait();
      const int par = krow & 1;
      uint32_t v0[16], v1[16], v2[16];
#pragma unroll
      for (int i = 0; i < 16; i++) {
        const uint32_t nx = __shfl_down_sync(0xffffffffu, ra[i].x, 1), ny = __shfl_down_sync(0xffffffffu, ra[i].y, 1);
        const uint32_t bx = lane == 31 ? rb[i].x : nx, by = lane == 31 ? rb[i].y : ny;
        v0[i] = (krow & 2) ? ra[i].y : ra[i].x;
        v1[i] = (krow & 2) ? bx : ra[i].y;
        v2[i] = (krow & 2) ? by : bx;
      }
      {
        const uint32_t mw = warp_max_exp(acc_max_exp(acc_max_exp(acc_max_exp(0u, v0), v1), v2));
        if (lane == 0) asm volatile("st.shared.b32 [%0], %1;" ::"r"(sb + OFF_TW2 + 448 + w4 * 4), "r"(mw) : "memory");
      }
      if (u == 63) {
        const uint32_t sn = par ? 0x4432u : 0x4410u;
#pragma unroll
        for (int i = 0; i < 16; i += 4)
          sts128(sb + OFF_TW2 + 256 + qh * 64 + i * 4, __byte_perm(v2[i], 0, sn), __byte_perm(v2[i + 1], 0, sn),
                 __byte_perm(v2[i + 2], 0, sn), __byte_perm(v2[i + 3], 0, sn));
      }
      if (par) {
#pragma unroll
        for (int i = 0; i < 16; i++) { const uint32_t ev = __byte_perm(v0[i], v1[i], 0x7632u); v1[i] = __byte_perm(v1[i], v2[i], 0x5410u); v0[i] = ev; }
      } else {
#pragma unroll
        for (int i = 0; i < 16; i++) { const uint32_t ev = __byte_perm(v0[i], v1[i], 0x5410u); v1[i] = __byte_perm(v0[i], v1[i], 0x7632u); v0[i] = ev; }
      }
      const uint32_t dst = sb + OFF_ST + (uint32_t)(32 * (u >> 4) + (u & 15)) * 128u;
      const uint32_t sw = (uint32_t)((qh * 4) ^ (u & 7));
      mbar_wait_u(BAR(B_TABFREE), 0);
#pragma unroll
      for (int i = 0; i < 16; i += 4) {
        sts128(dst + ((sw ^ (i >> 2)) << 4), v0[i], v0[i + 1], v0[i + 2], v0[i + 3]);
        sts128(dst + 2048 + ((sw ^ (i >> 2)) << 4), v1[i], v1[i + 1], v1[i + 2], v1[i + 3]);
      }
      fence_async_smem();
      mbar_arrive(BAR(B_WFULL));
      {
        const int gc0 = 2 * (lane & 3) + ((lane >> 2) & 1);
        const uint4 gwa = __ldg(reinterpret_cast<const uint4*>(gate_w) + 8 * (lane >> 2) + gc0);
        const uint4 gwb = __ldg(reinterpret_cast<const uint4*>(gate_w) + 8 * (lane >> 2) + (gc0 ^ 1));
        float d[4];
#pragma unroll
        for (int i = 0; i < 4; i++) {
          const int row = 4 * w4 + i;
          const uint32_t ad = sb + OFF_X + (lane >> 2) * 16384 + (uint32_t)(16 * j + row) * 128u + ((gc0 ^ (row & 7)) << 4);
          const uint4 xa = lds128(ad), xb = lds128(ad ^ 16);
          const uint32_t p0 = mul_bf16x2(xa.x, gwa.x), p1 = mul_bf16x2(xa.y, gwa.y), p2 = mul_bf16x2(xa.z, gwa.z), p3 = mul_bf16x2(xa.w, gwa.w);
          const uint32_t p4 = mul_bf16x2(xb.x, gwb.x), p5 = mul_bf16x2(xb.y, gwb.y), p6 = mul_bf16x2(xb.z, gwb.z), p7 = mul_bf16x2(xb.w, gwb.w);
          d[i] = (((bf_lo(p0) + bf_hi(p0)) + (bf_lo(p1) + bf_hi(p1))) + ((bf_lo(p2) + bf_hi(p2)) + (bf_lo(p3) + bf_hi(p3))))
               + (((bf_lo(p4) + bf_hi(p4)) + (bf_lo(p5) + bf_hi(p5))) + ((bf_lo(p6) + bf_hi(p6)) + (bf_lo(p7) + bf_hi(p7))));
        }
        float e0 = (lane & 1) ? d[1] : d[0], e1 = (lane & 1) ? d[3] : d[2];
        e0 += __shfl_xor_sync(0xffffffffu, (lane & 1) ? d[0] : d[1], 1);
        e1 += __shfl_xor_sync(0xffffffffu, (lane & 1) ? d[2] : d[3], 1);
        float f0 = (lane & 2) ? e1 : e0;
        f0 += __shfl_xor_sync(0xffffffffu, (lane & 2) ? e0 : e1, 2);
        f0 += __shfl_xor_sync(0xffffffffu, f0, 4);
        f0 += __shfl_xor_sync(0xffffffffu, f0, 8);
        f0 += __shfl_xor_sync(0xffffffffu, f0, 16);
        asm volatile("{\n.reg .pred p;\nsetp.lt.u32 p, %2, 4;\n@p st.shared.f32 [%0], %1;\n}" ::"r"(sb + OFF_TW2 + 384 + (4 * w4 + (lane & 3)) * 4), "f"(f0), "r"(lane) : "memory");
        __syncwarp();
        mbar_arrive_if(BAR(B_GDONE), lane == 0);
      }
    }
    asm volatile("setmaxnreg.inc.sync.aligned.u32 136;");
    __half2 tw1[16], tw2[16];
    const __half2 k6 = __float2half2_rn(1.0f / 64.0f), k4 = __float2half2_rn(1.0f / 16.0f);
    uint32_t twall = 0xFFFFFFFFu;
    float a1 = (float)t * (3.14159265358979f / 1024.0f), a2 = (float)q * (3.14159265358979f / 64.0f);
    asm volatile("" : "+f"(a1), "+f"(a2) :: "memory");
#pragma unroll
    for (int i = 1; i < 16; i++) {
      tw1[i] = __hmul2(__floats2half2_rn(__cosf(a1 * i), __sinf(a1 * i)), k6);
      tw2[i] = __hmul2(__floats2half2_rn(__cosf(a2 * i), __sinf(a2 * i)), k4);
      twall &= h2u(tw1[i]) & h2u(tw2[i]);
    }
    if (extra) {
      if (t128 == 0) {
        mbar_init(BAR(B_YRDY), 1);
        poll_counter(&g_Sync[1], 16 * e);
        poll_counter(&g_Fin[1], e);
        mbar_expect_tx(BAR(B_YRDY), 16384);
        bulk_load(sb + OFF_FF, g_Y, 16384, BAR(B_YRDY));
      }
      bar_sync(2, 128);
    }
    mbar_wait_u(BAR(B_YRDY), twall == 0xFFFFFFFFu);
    const uint32_t fbuf = sb + OFF_FF;
    const uint32_t x1 = (uint32_t)(k1 & 1) << 6;
    const uint32_t a_col = fbuf + (t ^ ((t >> 2) & 4)) * 8;
    const uint32_t a_row = fbuf + k1 * 1024 + x1 + q * 8;
    const uint32_t a_tr  = fbuf + k1 * 1024 + ((q * 64) ^ x1) + q * 8;
    C2 v[16];
    int ey;
    {
      uint32_t y[32];
      const uint32_t yl = fbuf + (uint32_t)(lane >> 3) * 512u + w4 * 128 + (lane & 7) * 16;
#pragma unroll
      for (int i = 0; i < 8; i++)
        asm volatile("ldmatrix.sync.aligned.m8n8.x4.shared.b16 {%0, %1, %2, %3}, [%4];"
                     : "=r"(y[4 * i]), "=r"(y[4 * i + 1]), "=r"(y[4 * i + 2]), "=r"(y[4 * i + 3]) : "r"(yl + i * 2048) : "memory");
      if (P == 0) {
#pragma unroll
        for (int n1 = 0; n1 < 16; n1++) {
          if (extra) { y[n1] = y[16 + n1] & 0xFFFFu; y[16 + n1] = 0; }
          else y[16 + n1] &= 0xFFFF0000u;
        }
      }
      const uint32_t my = warp_max_exp(acc_max_exp(0u, y));
      if (lane == 0) asm volatile("st.shared.b32 [%0], %1;" ::"r"(sb + OFF_TW2 + 464 + w4 * 4), "r"(my) : "memory");
      bar_sync(2, 128);
      const uint4 m1 = lds128(sb + OFF_TW2 + 464);
      ey = max((int)max(max(m1.x, m1.y), max(m1.z, m1.w)) - 18, 0);
      const uint32_t nby = ((uint32_t)(-(ey << 7)) & 0xFFFFu) * 0x10001u;
#pragma unroll
      for (int n1 = 0; n1 < 16; n1++) v[n1] = C2{u2h(bf2_to_h2(y[n1], nby)), u2h(bf2_to_h2(y[16 + n1], nby))};
    }
    fft16<-1>(v);
    v[0] = C2{__hmul2(v[0].x, k6), __hmul2(v[0].y, k6)};
#pragma unroll
    for (int i = 1; i < 16; i++) v[i] = ctw<-1>(v[i], tw1[i]);
#pragma unroll
    for (int i = 0; i < 16; i++) sts_c2((a_col ^ ((i & 1) << 6)) + i * 1024, v[i]);
    bar_sync(2, 128);
#pragma unroll
    for (int i = 0; i < 16; i++) v[i] = lds_c2((a_row ^ (((i & 1) << 6) | ((i & 2) << 4))) + (i >> 1) * 128);
    fft16<-1>(v);
    if (!extra) mbar_wait_u(BAR(B_WRDY), 0);
    const uint32_t exw = ld_relaxed(&g_Sync[17 * 32 + 2]), exx = ld_relaxed(&g_Sync[17 * 32 + 4]);
    uint32_t f[32];
    {
      const uint4* fsrc = g_W + (size_t)(extra ? 128 : P) * 1024 + t128;
#pragma unroll
      for (int i = 0; i < 8; i++) {
        const uint4 a = __ldcg(fsrc + i * 128);
        f[4 * i] = a.x; f[4 * i + 1] = a.y; f[4 * i + 2] = a.z; f[4 * i + 3] = a.w;
      }
    }
    v[0] = C2{__hmul2(v[0].x, k4), __hmul2(v[0].y, k4)};
#pragma unroll
    for (int i = 1; i < 16; i++) v[i] = ctw<-1>(v[i], tw2[i]);
    __syncwarp();
#pragma unroll
    for (int i = 0; i < 16; i++) sts_c2((a_row ^ (((i & 1) << 6) | ((i & 7) << 3))) + (i >> 1) * 128, v[i]);
    __syncwarp();
#pragma unroll
    for (int i = 0; i < 16; i++) v[i] = lds_c2((a_tr ^ ((i & 7) << 3)) + (i & 8) * 64);
    fft8<-1>(v);
    fft8<-1>(v + 8);
    __half2 zs;
    {
      const uint32_t ex = (exw & 0xFFu) | ((exx & 0xFFu) << 8);
      if (t128 == 0) reinterpret_cast<volatile uint32_t*>(smem + OFF_EXP)[0] = ex;
      const int ew = max((int)(ex & 0xFFu) - 22, 0), eref = max((int)((ex >> 8) & 0xFFu) - 12, 6);
      const uint32_t nbw = ((uint32_t)(-(ew << 7)) & 0xFFFFu) * 0x10001u;
#pragma unroll
      for (int i = 0; i < 32; i++) f[i] = bf2_to_h2(f[i], nbw);
      const float zf = __uint_as_float((uint32_t)max(127 + ey + 6 - eref, 1) << 23);
      zs = __float2half2_rn(zf);
      const __half2 zt = __float2half2_rn(zf * 64.0f);
#pragma unroll
      for (int i = 1; i < 16; i++) tw1[i] = __hmul2(tw1[i], zt);
    }
#define F_RE(i) u2h(f[2 * ((i) & ~1) + ((i) & 1)])
#define F_IM(i) u2h(f[2 * ((i) & ~1) + 2 + ((i) & 1)])
#pragma unroll
    for (int hh = 0; hh < 16; hh += 8) {
      C2 e[4], o[4];
#pragma unroll
      for (int b = 0; b < 4; b++)
        bfly_tw<1>(cmul<1>(v[hh + b], F_RE(hh + b), F_IM(hh + b)), v[hh + 4 + b], F_RE(hh + 4 + b), F_IM(hh + 4 + b), e[b], o[b]);
      fft8_second<1>(e, o, v + hh);
    }
#pragma unroll
    for (int i = 0; i < 16; i++) sts_c2((a_tr ^ ((i & 7) << 3)) + (i & 8) * 64, v[i]);
    __syncwarp();
#pragma unroll
    for (int i = 0; i < 16; i++) v[i] = lds_c2((a_row ^ (((i & 1) << 6) | ((i & 7) << 3))) + (i >> 1) * 128);
    v[0] = C2{__hmul2(v[0].x, k4), __hmul2(v[0].y, k4)};
    fft16_pre<1>(v, tw2);
    __syncwarp();
#pragma unroll
    for (int i = 0; i < 16; i++) sts_c2((a_row ^ (((i & 1) << 6) | ((i & 2) << 4))) + (i >> 1) * 128, v[i]);
    bar_sync(2, 128);
#pragma unroll
    for (int i = 0; i < 16; i++) v[i] = lds_c2((a_col ^ ((i & 1) << 6)) + i * 1024);
    v[0] = C2{__hmul2(v[0].x, zs), __hmul2(v[0].y, zs)};
    fft16_pre<1>(v, tw1);
    bar_sync(2, 128);
    {
      const uint32_t zst = fbuf + (uint32_t)(((lane >> 3) & 1) * 2 + (lane & 1)) * 4160u
                         + (uint32_t)(128 * (lane >> 4) + 32 * w4 + 8 * ((lane >> 1) & 3)) * 2u;
#pragma unroll
      for (int n1 = 0; n1 < 16; n1 += 2)
        asm volatile("stmatrix.sync.aligned.m8n8.x4.trans.shared.b16 [%0], {%1, %2, %3, %4};"
                     ::"r"(zst + n1 * 256), "r"(h2u(v[n1].x)), "r"(h2u(v[n1].y)), "r"(h2u(v[n1 + 1].x)), "r"(h2u(v[n1 + 1].y)) : "memory");
    }
    fence_async_smem();
    bar_sync(2, 128);
    if (t128 == 0) {
      if (!extra) mbar_arrive(BAR(B_FFTOUT));
      uint16_t* zrow = g_Z + (size_t)(16 * (P >> 2) + 2 * (P & 3)) * 2048;
      if (extra) {
        bulk_store(zrow + 2048, fbuf, 4096);
      } else {
#pragma unroll 1
        for (int row = 0; row < 4; row++)
          if (P != 0 || row != 2) bulk_store(zrow + ((row & 1) * 8 + (row >> 1)) * 2048, fbuf + row * 4160, 4096);
        bulk_commit();
        bulk_wait_read();
      }
      bulk_commit();
      if (!extra) mbar_arrive(BAR(B_FFDONE));
      if (!extra) mbar_wait(BAR(B_HDONE), 0);
      bulk_wait_all();
      if (!extra) mbar_arrive(BAR(B_ZPUB));
      if (extra) g_Sync[blockIdx.x * 32] = e;
    }
    __syncwarp();
    if (t128 < (extra ? 16 : 17))
      red_relaxed(&g_Rdy[t128 < 16 ? (2 * t128 + ((P >> 4) & 1)) * 32 + 14 + (P >> 5) : (2 * r + (j >> 2)) * 32 + 12 + ((j >> 1) & 1)]);
  } else {
    asm volatile("setmaxnreg.dec.sync.aligned.u32 40;");
    if (extra) return;
    if (warp == 12) {
      cluster_wait();
      const CUtensorMap* wm = kh ? &map_wu : &map_wg;
      const CUtensorMap* wn = kh ? &map_un : &map_gn;
      mbar_wait_u(BAR(B_XFULL + 3), 0);
#pragma unroll 1
      for (int n = 0; n < 28; n++) {
        const int tile = n >> 3, slot = n & 3;
        int c0 = g1_chunk(j, tile) * 64 + (tile == 3 ? (j & 1) * 32 : 0), c1 = (n & 7) * (tile == 3 ? 128 : 64);
        uint32_t full = BAR(B_RFULL + ((tile & 1) ^ 1) * 4 + slot), dst = sb + OFF_R + slot * 16384 + kh * 8192;
        const CUtensorMap* m = tile == 3 ? wn : wm;
        if (n == 16) asm volatile("prefetch.tensormap [%0];" ::"l"(wn) : "memory");
        asm volatile("" : "+r"(c0), "+r"(c1), "+r"(full), "+r"(dst), "+l"(m));
        mbar_wait_u(BAR(B_REMPTY + slot), ((n >> 2) & 1) ^ 1);
        mbar_expect_tx_e(full, 16384);
        tma2d_mc_e(dst, m, c0, c1, full);
      }
      mbar_wait_u(BAR(B_STFULL + 4), 0);
#pragma unroll 1
      for (int q = 0; q < 8192; q += 4096) {
        asm volatile(ELECT "cp.async.bulk.global.shared::cta.bulk_group [%0], [%1], %2;\n}"
                     ::"l"(g_H + (size_t)(r * 28 + g1_chunk(j, 3)) * 16384 + (j & 1) * 8192 + q), "r"(sb + OFF_NST + q), "r"(4096) : "memory");
        bulk_commit();
        bulk_wait_read();
      }
      __syncwarp();
      mbar_arrive_if(BAR(B_G2EMPTY + 5), lane == 0);
      mbar_arrive_remote_if(mapa(BAR(B_G2EMPTY + 5), kh ^ 1), lane == 0);
      bulk_wait_done();
      asm volatile(ELECT "mbarrier.arrive.shared::cta.b64 _, [%0];\n}" ::"r"(BAR(B_HDONE)) : "memory");
      mbar_wait_u(BAR(B_WRDY), 0);
#pragma unroll 1
      for (int z = 0; z < 4; z++) {
        if (!(z & 1)) mbar_wait_u(BAR(z ? B_FFDONE : B_STEMPTY + 4), 0);
        mbar_expect_tx_e(BAR(B_ZFULL + z), 8192);
        bulk_load_e(sb + OFF_ST + z * 8192, g_T + (size_t)((2 * z + kq) * 4 + p) * 8192, 8192, BAR(B_ZFULL + z));
      }
    } else if (warp == 13) {
      bar_arrive(6, 64);
      cluster_wait();
      {
        const unsigned e = __ldcg(&g_Sync[blockIdx.x * 32]) + 1;
        const int wl = ((int)blockIdx.x & 7) * 16 + ((int)blockIdx.x >> 3);
        mbar_wait_u(BAR(B_WFULL), 0);
        mbar_wait_u(BAR(B_YMAX), 0);
        const uint4 m4 = lds128(sb + OFF_TW2 + 448 + (lane & 1) * 32);
        unsigned long long* gmax = reinterpret_cast<unsigned long long*>(&g_Sync[17 * 32 + 2]) + (lane & 1);
        unsigned long long tag = ((unsigned long long)e << 8) | max(max(m4.x, m4.y), max(m4.z, m4.w)), prevm = 0;
        asm volatile("{\n.reg .pred p;\nsetp.lt.u32 p, %3, 2;\n@p atom.relaxed.gpu.global.max.u64 %0, [%1], %2;\n}"
                     : "+l"(prevm) : "l"(gmax), "l"(tag), "r"(lane) : "memory");
        asm volatile(ELECT "cp.async.bulk.global.shared::cta.bulk_group [%0], [%1], 128;\n}"
                     ::"l"(g_W + ((size_t)128 * 128 + wl) * 8), "r"(sb + OFF_TW2 + 256) : "memory");
#pragma unroll 1
        for (int c = 0; c < 4; c++) {
          asm volatile(ELECT "cp.async.bulk.tensor.2d.global.shared::cta.bulk_group [%0, {%1, %2}], [%3];\n}"
                       ::"l"(&map_w), "r"(wl * 64), "r"(c * 32), "r"(sb + OFF_ST + c * 4096) : "memory");
          bulk_commit();
          bulk_wait_read();
        }
        mbar_arrive_if(BAR(B_STEMPTY + 1), lane == 0);
        bulk_wait_all();
        unsigned old = 0;
        const bool go = __all_sync(0xffffffffu, (unsigned)(prevm >> 32) != 0xFFFFFFFFu) && lane == 0;
        asm volatile("{\n.reg .pred p;\nsetp.ne.u32 p, %2, 0;\n@p atom.relaxed.gpu.global.add.u32 %0, [%1], 1;\n}"
                     : "+r"(old) : "l"(&g_Sync[16 * 32 + 1]), "r"((uint32_t)go) : "memory");
        old = __shfl_sync(0xffffffffu, old, 0);
        asm volatile("{\n.reg .pred p;\nsetp.ne.u32 p, %2, 0;\n@p st.relaxed.gpu.global.u32 [%0], %1;\n}"
                     ::"l"(&g_Fin[(lane & 15) * 32 + 1]), "r"(e), "r"((uint32_t)(old + 1 == 128 * e && lane < 16)) : "memory");
      }
      {
        sts128(sb + OFF_ZERO + lane * 16, 0u, 0u, 0u, 0u);
        sts128(sb + OFF_ZERO + 512 + lane * 16, 0u, 0u, 0u, 0u);
        fence_async_smem();
        __syncwarp();
        const __nv_bfloat16* orow = out + (size_t)(r * 128 + 16 * j) * 512;
#pragma unroll 1
        for (int i = 0; i < 16; i++) {
          asm volatile(ELECT "cp.async.bulk.global.shared::cta.bulk_group [%0], [%1], 1024;\n}"
                       ::"l"(orow + i * 512), "r"(sb + OFF_ZERO) : "memory");
          if (i & 1) { bulk_commit(); bulk_wait_read(); }
        }
        bulk_wait_done();
        __syncwarp();
      }
      {
        mbar_wait_u(BAR(B_GDONE), 0);
        const float logit = bf_lo(pack_bf16(reinterpret_cast<const float*>(smem + OFF_TW2 + 384)[lane & 15], 0.f));
        const float gv = bf_lo(pack_bf16(__fdividef(1.0f, 1.0f + __expf(-logit)), 0.f));
        asm volatile("{\n.reg .pred p;\nsetp.lt.u32 p, %2, 16;\n@p st.global.cg.f32 [%0], %1;\n}"
                     ::"l"(&g_G[r * 128 + 16 * j + (lane & 15)]), "f"(gv), "r"(lane) : "memory");
        __syncwarp();
        asm volatile("{\n.reg .pred p;\nsetp.lt.u32 p, %1, 2;\n@p red.release.gpu.global.add.u32 [%0], 1;\n}"
                     ::"l"(&g_Rdy[(2 * r + (lane & 1)) * 32 + 18]), "r"(lane) : "memory");
      }
      uint32_t ready = 0;
      const int n0 = p * 64 + (kh ^ kq) * 256;
#define WAIT_READY(i) do { uint32_t n_ = 0;                                                \
        while (!((ready >> (i)) & 1)) {                                                      \
          ready = __shfl_sync(0xffffffffu, ld_volatile_shared(sb + OFF_READY), 0);           \
          if (++n_ > (SPIN_LIMIT << 4)) __trap();                                            \
        } } while (0)
#pragma unroll 1
      for (int i = 0; i < 14; i++) {
        const int chunk = g2_chunk(kq, i);
        const uint32_t b = g2_seq(i) & 7u, ph = g2_seq(i) >> 3;
        uint32_t buf = sb + g2_buf(b), full = BAR(B_G2FULL + b);
        int c1 = chunk * 64;
        if (i == 10) {
          asm volatile("prefetch.tensormap [%0];" ::"l"(&map_z) : "memory");
          asm volatile("prefetch.tensormap [%0];" ::"l"(&map_o) : "memory");
        }
        const uint8_t* src = g_H + (size_t)(r * 28 + chunk) * 16384;
        asm volatile("" : "+r"(c1), "+r"(full), "+r"(buf), "+l"(src));
        if (i == LD_GATE) mbar_wait_u(BAR(B_ZPUB), 0);
        mbar_wait_u(BAR(B_G2EMPTY + b), ph);
        mbar_expect_tx_e(full, 32768);
        tma2d_mc_e(buf + 16384 + kh * 8192, &map_wd, n0, c1, full);
        WAIT_READY(i);
        bulk_load_e(buf, src, 16384, full);
      }
#pragma unroll 1
      for (int z = 0; z < 4; z++) {
        if (!(z & 1)) mbar_wait_u(BAR(B_G2EMPTY + (z ? 3 : 2)), 0);
        WAIT_READY(14 + z);
        mbar_expect_tx_e(BAR(B_ZFULL + z), 16384);
        tma2d_e(sb + z_buf(z), &map_z, r * 128, (2 * z + kq) * 64, BAR(B_ZFULL + z));
        tma2d_e(sb + z_buf(z) + 8192, &map_z, r * 128 + 64, (2 * z + kq) * 64, BAR(B_ZFULL + z));
      }
    } else if (warp == 14) {
      if (lane == 0) {
        asm volatile("prefetch.tensormap [%0];" ::"l"(&map_w) : "memory");
        asm volatile("prefetch.tensormap [%0];" ::"l"(&map_y) : "memory");
        asm volatile("prefetch.tensormap [%0];" ::"l"(&map_wd) : "memory");
        asm volatile("prefetch.tensormap [%0];" ::"l"(&map_z) : "memory");
      }
      __syncwarp();
      cluster_wait();
      if (lane == 0) {
        mbar_wait(BAR(B_STFULL + 0), 0);
#pragma unroll 1
        for (int q = 0; q < 4; q++) {
          tma2d_store(&map_y, r * 256 + q * 64, j * 32, sb + OFF_FF + q * 4096);
          bulk_commit();
          bulk_wait_read();
        }
        mbar_arrive(BAR(B_FFFREE));
        bulk_wait_all();
        red_relaxed(&g_Sync[j * 32 + 1]);
#pragma unroll 1
        for (int ev = 1; ev < 4; ev++) {
          uint8_t* dst = g_H + (size_t)(r * 28 + g1_chunk(j, ev - 1)) * 16384;
          mbar_wait(BAR(B_STFULL + ev), 0);
#pragma unroll 1
          for (int q = 0; q < 16384; q += 4096) {
            bulk_store(dst + q, sb + OFF_ST + q, 4096);
            bulk_commit();
            bulk_wait_read();
          }
          mbar_arrive(BAR(B_STEMPTY + 1 + ev));
          bulk_wait_all();
          red_relaxed(&g_Rdy[(2 * r + (j & 1)) * 32 + 4 * ev - 4 + (j >> 1)]);
        }
      }
    } else {
      const unsigned e = __ldcg(&g_Sync[blockIdx.x * 32]) + 1;
      bar_sync(6, 64);
      cluster_wait();
      if (lane == 0) {
        const CUtensorMap* wm = kh ? &map_wu : &map_wg;
        const int c1 = (r >> 1) * 64;
        mbar_wait(BAR(B_XFULL + 7), 0);
        tma2d_prefetch(wm, g1_chunk(j, 1) * 64, c1);
        mbar_wait(BAR(B_TABFREE), 0);
        tma2d_prefetch(wm, g1_chunk(j, 2) * 64, c1);
        mbar_wait(BAR(B_STFULL + 0), 0);
        mbar_expect_tx(BAR(B_YRDY), 16384);
        mbar_wait(BAR(B_FFFREE), 0);
        poll_counter(&g_Sync[((int)blockIdx.x >> 4) * 32 + 1], 16 * e);
        bulk_load(sb + OFF_FF, g_Y + (size_t)blockIdx.x * 4096, 16384, BAR(B_YRDY));
        tma2d_prefetch(wm, g1_chunk(j, 3) * 64, c1);
        poll_counter(&g_Fin[((int)blockIdx.x >> 3) * 32 + 1], e);
        mbar_arrive(BAR(B_WRDY));
        bulk_prefetch(wd_ptr + (size_t)blockIdx.x * 7168, 14336);
      }
      __syncwarp();
      const int i = lane < 19 ? lane : 0;
      bool gload = false;
      const unsigned target = ((i == 12 || i == 13) ? 2 : i == 18 ? 8 : i < 14 ? 1 : (i == 14 && kq == 0) ? 17 : 16) * e;
      const unsigned* cptr = &g_Rdy[(2 * r + kq) * 32 + i];
      uint32_t ready = 0, n = 0;
      unsigned pv = ld_relaxed(cptr);
      while (ready != 0xffffffffu) {
        ready |= __ballot_sync(0xffffffffu, (int)(pv - target) >= 0);
        if (!((ready >> lane) & 1)) pv = ld_relaxed(cptr);
        if (lane == 0) asm volatile("st.volatile.shared.b32 [%0], %1;" ::"r"(sb + OFF_READY), "r"(ready) : "memory");
        if (++n > SPIN_LIMIT) __trap();
        if (!gload && (ready & 0x40000u)) {
          gload = true;
          reinterpret_cast<float4*>(smem + OFF_G)[lane] = __ldcg(reinterpret_cast<const float4*>(g_G + r * 128) + lane);
          mbar_arrive(BAR(B_GFULL));
        }
      }
      if (lane == 0) g_Sync[blockIdx.x * 32] = e;
    }
  }
#undef BAR
}

typedef CUresult (*EncodeFn)(CUtensorMap*, CUtensorMapDataType, cuuint32_t, void*, const cuuint64_t*, const cuuint64_t*,
                             const cuuint32_t*, const cuuint32_t*, CUtensorMapInterleave, CUtensorMapSwizzle,
                             CUtensorMapL2promotion, CUtensorMapFloatOOBfill);

void make_map(EncodeFn enc, CUtensorMap* m, const void* ptr, uint64_t inner, uint64_t outer, uint32_t box_outer,
              uint32_t box_inner = 64) {
  cuuint64_t dims[2] = {inner, outer};
  cuuint64_t strides[1] = {inner * 2};
  cuuint32_t box[2] = {box_inner, box_outer};
  cuuint32_t es[2] = {1, 1};
  enc(m, CU_TENSOR_MAP_DATA_TYPE_BFLOAT16, 2, const_cast<void*>(ptr), dims, strides, box, es, CU_TENSOR_MAP_INTERLEAVE_NONE,
      box_inner == 64 ? CU_TENSOR_MAP_SWIZZLE_128B : CU_TENSOR_MAP_SWIZZLE_64B, CU_TENSOR_MAP_L2_PROMOTION_L2_128B, CU_TENSOR_MAP_FLOAT_OOB_FILL_NONE);
}

}

extern "C" void kernel_launch(void* const* d_in, const int* in_sizes, int n_in, void* d_out, int out_size) {
  static EncodeFn enc = nullptr;
  if (!enc) {
    void* fn = nullptr;
    cudaDriverEntryPointQueryResult q;
    cudaGetDriverEntryPoint("cuTensorMapEncodeTiled", &fn, cudaEnableDefault, &q);
    enc = (EncodeFn)fn;
    cudaFuncSetAttribute(fused_kernel, cudaFuncAttributeMaxDynamicSharedMemorySize, SMEM_BYTES);
  }
  const __nv_bfloat16* x  = (const __nv_bfloat16*)d_in[0];
  const __nv_bfloat16* wr = (const __nv_bfloat16*)d_in[1];
  const __nv_bfloat16* wi = (const __nv_bfloat16*)d_in[2];
  const __nv_bfloat16* wg = (const __nv_bfloat16*)d_in[4];
  const __nv_bfloat16* wu = (const __nv_bfloat16*)d_in[5];
  const __nv_bfloat16* wd = (const __nv_bfloat16*)d_in[6];
  const __nv_bfloat16* gw = (const __nv_bfloat16*)d_in[7];
  void *yp = nullptr, *zp = nullptr, *wp = nullptr;
  cudaGetSymbolAddress(&wp, g_W);
  cudaGetSymbolAddress(&yp, g_Y);
  cudaGetSymbolAddress(&zp, g_Z);
  CUtensorMap mx, mg, mu, md, my, mz, mw, mgn, mun, mo;
  make_map(enc, &mo, d_out, 512, 2048, 16);
  make_map(enc, &mgn, wg, 1792, 512, 128, 32);
  make_map(enc, &mun, wu, 1792, 512, 128, 32);
  make_map(enc, &mw, wp, 8192, 128, 32);
  make_map(enc, &my, yp, 4096, 256, 32);
  make_map(enc, &mz, zp, 2048, 512, 64);
  make_map(enc, &mx, x, 512, 2048, 128);
  make_map(enc, &mg, wg, 1792, 512, 64);
  make_map(enc, &mu, wu, 1792, 512, 64);
  make_map(enc, &md, wd, 512, 1792, 64);
  fused_kernel<<<130, 512, SMEM_BYTES>>>(mx, mg, mu, md, my, mz, mw, mgn, mun, mo, x, wr, wi, wd, gw, (__nv_bfloat16*)d_out);
}
```
